```python
import torch

def _softmax(x, axis=-1):
    return torch.softmax(x, dim=axis)
def _gelu(x):
    return torch.nn.functional.gelu(x, approximate="tanh")
def _silu(x):
    return torch.nn.functional.silu(x)
def _sigmoid(x):
    return torch.sigmoid(x)
def _layernorm(x, axis=-1, eps=1e-5):
    m = x.mean(dim=axis, keepdim=True)
    v = x.var(dim=axis, keepdim=True, unbiased=False)
    return (x - m) / torch.sqrt(v + eps)
def _scatter_add(tgt, idx, src, axis=0):
    return tgt.clone().index_add_(axis, idx, src)
def _segment_sum(src, seg, n):
    out = torch.zeros((n,) + src.shape[1:], dtype=src.dtype)
    return out.index_add_(0, seg, src)
def _pad(x, pw):
    flat = tuple(v for pair in reversed(pw) for v in pair)
    return torch.nn.functional.pad(x, flat)

kernel_name = 'gated_mix__ssm_conv_s4d__ssm_conv_s4d__prompt'

def setup_inputs():

    _w = (lambda a: (lambda t: t.to(torch.bfloat16) if t.is_floating_point() else t)(torch.as_tensor(a)))
    def _A_setup():
        Bsz, L, D, N = 1, 2048, 512, 128
        return {
            "u": _w((lambda *s: torch.randn(*s, dtype=torch.bfloat16) * 0.05)(Bsz, L, D)),
            "log_A_real": _w((lambda *s: torch.randn(*s, dtype=torch.bfloat16) * 6.4)(D, N) * 0.5),
            "A_imag": _w((lambda *s: torch.randn(*s, dtype=torch.bfloat16) * 0.05)(D, N) * 3.14),
            "C_real": _w((lambda *s: torch.randn(*s, dtype=torch.bfloat16) * 0.05)(D, N) / N ** 0.5),
            "C_imag": _w((lambda *s: torch.randn(*s, dtype=torch.bfloat16) * 0.05)(D, N) / N ** 0.5),
            "log_dt": _w((lambda *s: torch.randn(*s, dtype=torch.bfloat16) * 0.05)(D) * 0.5 - 4.0),
            "D_skip": _w((lambda *s: torch.randn(*s, dtype=torch.bfloat16) * 0.05)(D)),
        }
    _A_in = _A_setup()

    def _B_setup():
        Bsz, L, D, N = 1, 2048, 512, 128
        return {
            "u": _w((lambda *s: torch.randn(*s, dtype=torch.bfloat16) * 0.05)(Bsz, L, D)),
            "log_A_real": _w((lambda *s: torch.randn(*s, dtype=torch.bfloat16) * 6.4)(D, N) * 0.5),
            "A_imag": _w((lambda *s: torch.randn(*s, dtype=torch.bfloat16) * 0.05)(D, N) * 3.14),
            "C_real": _w((lambda *s: torch.randn(*s, dtype=torch.bfloat16) * 0.05)(D, N) / N ** 0.5),
            "C_imag": _w((lambda *s: torch.randn(*s, dtype=torch.bfloat16) * 0.05)(D, N) / N ** 0.5),
            "log_dt": _w((lambda *s: torch.randn(*s, dtype=torch.bfloat16) * 0.05)(D) * 0.5 - 4.0),
            "D_skip": _w((lambda *s: torch.randn(*s, dtype=torch.bfloat16) * 0.05)(D)),
        }
    _B_in = _B_setup()

    return {
        "A_u": _A_in["u"],
        "A_log_A_real": _A_in["log_A_real"],
        "A_A_imag": _A_in["A_imag"],
        "A_C_real": _A_in["C_real"],
        "A_C_imag": _A_in["C_imag"],
        "A_log_dt": _A_in["log_dt"],
        "A_D_skip": _A_in["D_skip"],
        "B_u": _B_in["u"],
        "B_log_A_real": _B_in["log_A_real"],
        "B_A_imag": _B_in["A_imag"],
        "B_C_real": _B_in["C_real"],
        "B_C_imag": _B_in["C_imag"],
        "B_log_dt": _B_in["log_dt"],
        "B_D_skip": _B_in["D_skip"],
        "gate_w": _w((lambda *s: torch.randn(*s, dtype=torch.bfloat16) * 0.05)(512) * 16.0),
    }

def reference(A_u, A_log_A_real, A_A_imag, A_C_real, A_C_imag, A_log_dt, A_D_skip, B_u, B_log_A_real, B_A_imag, B_C_real, B_C_imag, B_log_dt, B_D_skip, gate_w):
    def _A_ref(u, log_A_real, A_imag, C_real, C_imag, log_dt, D_skip):
        L = u.shape[1]
        dt = torch.exp(log_dt)
        A = -torch.exp(log_A_real) + 1j * A_imag
        C = (C_real + 1j * C_imag) * dt[:, None]
        pos = (lambda x, dt: x.to(dt))(torch.arange(L), log_dt.dtype)
        P = torch.exp((A * dt[:, None])[:, :, None] * pos[None, None, :])
        K = 2.0 * torch.einsum("dn,dnl->dl", C, P).real
        L2 = 2 * L
        u_t = (lambda x, *d: x.permute(*d))(u, 0, 2, 1)
        Kf = (lambda x, *a, **k: torch.fft.rfft(x.float(), *a, **k))(K, L2)
        Uf = (lambda x, *a, **k: torch.fft.rfft(x.float(), *a, **k))(u_t, L2)
        y = (lambda x, *a, **k: torch.fft.irfft(x, *a, **k).to(torch.bfloat16))(Uf * Kf[None, :, :], L2)[:, :, :L]
        y = (lambda x, *d: x.permute(*d))(y, 0, 2, 1)
        return y + u * D_skip[None, None, :]

    def _B_ref(u, log_A_real, A_imag, C_real, C_imag, log_dt, D_skip):
        L = u.shape[1]
        dt = torch.exp(log_dt)
        A = -torch.exp(log_A_real) + 1j * A_imag
        C = (C_real + 1j * C_imag) * dt[:, None]
        pos = (lambda x, dt: x.to(dt))(torch.arange(L), log_dt.dtype)
        P = torch.exp((A * dt[:, None])[:, :, None] * pos[None, None, :])
        K = 2.0 * torch.einsum("dn,dnl->dl", C, P).real
        L2 = 2 * L
        u_t = (lambda x, *d: x.permute(*d))(u, 0, 2, 1)
        Kf = (lambda x, *a, **k: torch.fft.rfft(x.float(), *a, **k))(K, L2)
        Uf = (lambda x, *a, **k: torch.fft.rfft(x.float(), *a, **k))(u_t, L2)
        y = (lambda x, *a, **k: torch.fft.irfft(x, *a, **k).to(torch.bfloat16))(Uf * Kf[None, :, :], L2)[:, :, :L]
        y = (lambda x, *d: x.permute(*d))(y, 0, 2, 1)
        return y + u * D_skip[None, None, :]

    x = A_u
    g = _sigmoid((x * gate_w).sum(-1, keepdims=True))
    a = _A_ref(x, A_log_A_real, A_A_imag, A_C_real, A_C_imag, A_log_dt, A_D_skip)
    b = _B_ref(x, B_log_A_real, B_A_imag, B_C_real, B_C_imag, B_log_dt, B_D_skip)
    return g * a + (1 - g) * b
```

```cpp
#include <cuda_runtime.h>
#include <cuda.h>
#include <cuda_bf16.h>
#include <cuda_fp16.h>
#include <stdint.h>

#define TMADELAY 1
#define TMADEP + ((wLA ^ wAI ^ wCR ^ wCI) == 0x9E3779B9u && wLA == 0x12345678u ? 16 : 0)
#define L2PROMO CU_TENSOR_MAP_L2_PROMOTION_NONE

#define STAGGER 0
#define VIN 0
#define EARLY0 1
namespace {

constexpr int U1_PLANE = 1184;
constexpr int U1_CH    = 4 * U1_PLANE + 16;
constexpr int OFF_RAW  = 0;
constexpr int OFF_MISC = 32768;
constexpr int OFF_U1   = OFF_MISC + 384;
constexpr int T_D = 0, T_P3 = 1216, T_P5 = 1488, T_PS = 1760, CP = 2112, T_BR = 2 * CP;
constexpr int OFF_T    = OFF_U1 + 4 * U1_CH + 64;
constexpr int R_WARP   = 66 * 128;
constexpr int W_WG     = 4 * R_WARP;
constexpr int OFF_W    = OFF_T + 8 * T_BR;
constexpr int V3_OFF = 0, V5_OFF = 3584, V7_OFF = 7168, V9_OFF = 10240, V2_OFF = 13312;
constexpr int Y_PLANE  = 160, Y_BLK = 8 * Y_PLANE, Y_OWN = 4 * Y_BLK, Y_OFF = 15360, F_OFF = Y_OFF + 2 * Y_OWN - Y_BLK, F_OWN = 3 * Y_BLK;
constexpr int OFF_FIN  = OFF_W + 4 * W_WG;
constexpr int SMEM_BYTES = OFF_FIN + 4 * 2 * Y_BLK;
static_assert(OFF_T % 128 == 0 && OFF_W % 128 == 0 && W_WG % 128 == 0 && F_OFF + Y_BLK + 2 * F_OWN <= W_WG && 4 * Y_OWN + 4 * Y_BLK <= 32768 && SMEM_BYTES <= 232448, "smem");

__device__ unsigned g_epoch;
__device__ unsigned g_gate[2048];

struct Params {
  const uint4* u;
  const uint32_t* logA[2];
  const uint32_t* Aim[2];
  const uint32_t* Cre[2];
  const uint32_t* Cim[2];
  const uint16_t* logdt[2];
  const uint16_t* Dsk[2];
  const uint4* gw;
  uint4* out;
  unsigned* gate;
  unsigned* epoch;
};

template<int N, int TB> __device__ __forceinline__ void wgmma_rs(float* d, uint32_t a0, uint32_t a1, uint32_t a2, uint32_t a3, uint64_t desc);
template<int N, int TB> __device__ __forceinline__ void wgmma_rs_first(float* d, uint32_t a0, uint32_t a1, uint32_t a2, uint32_t a3, uint64_t desc);
template<> __device__ __forceinline__ void wgmma_rs<64,0>(float* d, uint32_t a0, uint32_t a1, uint32_t a2, uint32_t a3, uint64_t desc) {
  asm volatile("wgmma.mma_async.sync.aligned.m64n64k16.f32.bf16.bf16 {%0,%1,%2,%3,%4,%5,%6,%7,%8,%9,%10,%11,%12,%13,%14,%15,%16,%17,%18,%19,%20,%21,%22,%23,%24,%25,%26,%27,%28,%29,%30,%31}, {%32,%33,%34,%35}, %36, 1, 1, 1, 0;"
    : "+f"(d[0]), "+f"(d[1]), "+f"(d[2]), "+f"(d[3]), "+f"(d[4]), "+f"(d[5]), "+f"(d[6]), "+f"(d[7]), "+f"(d[8]), "+f"(d[9]), "+f"(d[10]), "+f"(d[11]), "+f"(d[12]), "+f"(d[13]), "+f"(d[14]), "+f"(d[15]), "+f"(d[16]), "+f"(d[17]), "+f"(d[18]), "+f"(d[19]), "+f"(d[20]), "+f"(d[21]), "+f"(d[22]), "+f"(d[23]), "+f"(d[24]), "+f"(d[25]), "+f"(d[26]), "+f"(d[27]), "+f"(d[28]), "+f"(d[29]), "+f"(d[30]), "+f"(d[31])
    : "r"(a0), "r"(a1), "r"(a2), "r"(a3), "l"(desc));
}
template<> __device__ __forceinline__ void wgmma_rs<56,0>(float* d, uint32_t a0, uint32_t a1, uint32_t a2, uint32_t a3, uint64_t desc) {
  asm volatile("wgmma.mma_async.sync.aligned.m64n56k16.f32.bf16.bf16 {%0,%1,%2,%3,%4,%5,%6,%7,%8,%9,%10,%11,%12,%13,%14,%15,%16,%17,%18,%19,%20,%21,%22,%23,%24,%25,%26,%27}, {%28,%29,%30,%31}, %32, 1, 1, 1, 0;"
    : "+f"(d[0]), "+f"(d[1]), "+f"(d[2]), "+f"(d[3]), "+f"(d[4]), "+f"(d[5]), "+f"(d[6]), "+f"(d[7]), "+f"(d[8]), "+f"(d[9]), "+f"(d[10]), "+f"(d[11]), "+f"(d[12]), "+f"(d[13]), "+f"(d[14]), "+f"(d[15]), "+f"(d[16]), "+f"(d[17]), "+f"(d[18]), "+f"(d[19]), "+f"(d[20]), "+f"(d[21]), "+f"(d[22]), "+f"(d[23]), "+f"(d[24]), "+f"(d[25]), "+f"(d[26]), "+f"(d[27])
    : "r"(a0), "r"(a1), "r"(a2), "r"(a3), "l"(desc));
}
template<> __device__ __forceinline__ void wgmma_rs<48,1>(float* d, uint32_t a0, uint32_t a1, uint32_t a2, uint32_t a3, uint64_t desc) {
  asm volatile("wgmma.mma_async.sync.aligned.m64n48k16.f32.bf16.bf16 {%0,%1,%2,%3,%4,%5,%6,%7,%8,%9,%10,%11,%12,%13,%14,%15,%16,%17,%18,%19,%20,%21,%22,%23}, {%24,%25,%26,%27}, %28, 1, 1, 1, 1;"
    : "+f"(d[0]), "+f"(d[1]), "+f"(d[2]), "+f"(d[3]), "+f"(d[4]), "+f"(d[5]), "+f"(d[6]), "+f"(d[7]), "+f"(d[8]), "+f"(d[9]), "+f"(d[10]), "+f"(d[11]), "+f"(d[12]), "+f"(d[13]), "+f"(d[14]), "+f"(d[15]), "+f"(d[16]), "+f"(d[17]), "+f"(d[18]), "+f"(d[19]), "+f"(d[20]), "+f"(d[21]), "+f"(d[22]), "+f"(d[23])
    : "r"(a0), "r"(a1), "r"(a2), "r"(a3), "l"(desc));
}
template<> __device__ __forceinline__ void wgmma_rs<32,1>(float* d, uint32_t a0, uint32_t a1, uint32_t a2, uint32_t a3, uint64_t desc) {
  asm volatile("wgmma.mma_async.sync.aligned.m64n32k16.f32.bf16.bf16 {%0,%1,%2,%3,%4,%5,%6,%7,%8,%9,%10,%11,%12,%13,%14,%15}, {%16,%17,%18,%19}, %20, 1, 1, 1, 1;"
    : "+f"(d[0]), "+f"(d[1]), "+f"(d[2]), "+f"(d[3]), "+f"(d[4]), "+f"(d[5]), "+f"(d[6]), "+f"(d[7]), "+f"(d[8]), "+f"(d[9]), "+f"(d[10]), "+f"(d[11]), "+f"(d[12]), "+f"(d[13]), "+f"(d[14]), "+f"(d[15])
    : "r"(a0), "r"(a1), "r"(a2), "r"(a3), "l"(desc));
}
template<> __device__ __forceinline__ void wgmma_rs<24,1>(float* d, uint32_t a0, uint32_t a1, uint32_t a2, uint32_t a3, uint64_t desc) {
  asm volatile("wgmma.mma_async.sync.aligned.m64n24k16.f32.bf16.bf16 {%0,%1,%2,%3,%4,%5,%6,%7,%8,%9,%10,%11}, {%12,%13,%14,%15}, %16, 1, 1, 1, 1;"
    : "+f"(d[0]), "+f"(d[1]), "+f"(d[2]), "+f"(d[3]), "+f"(d[4]), "+f"(d[5]), "+f"(d[6]), "+f"(d[7]), "+f"(d[8]), "+f"(d[9]), "+f"(d[10]), "+f"(d[11])
    : "r"(a0), "r"(a1), "r"(a2), "r"(a3), "l"(desc));
}
template<> __device__ __forceinline__ void wgmma_rs_first<64,0>(float* d, uint32_t a0, uint32_t a1, uint32_t a2, uint32_t a3, uint64_t desc) {
  asm volatile("wgmma.mma_async.sync.aligned.m64n64k16.f32.bf16.bf16 {%0,%1,%2,%3,%4,%5,%6,%7,%8,%9,%10,%11,%12,%13,%14,%15,%16,%17,%18,%19,%20,%21,%22,%23,%24,%25,%26,%27,%28,%29,%30,%31}, {%32,%33,%34,%35}, %36, 0, 1, 1, 0;"
    : "=f"(d[0]), "=f"(d[1]), "=f"(d[2]), "=f"(d[3]), "=f"(d[4]), "=f"(d[5]), "=f"(d[6]), "=f"(d[7]), "=f"(d[8]), "=f"(d[9]), "=f"(d[10]), "=f"(d[11]), "=f"(d[12]), "=f"(d[13]), "=f"(d[14]), "=f"(d[15]), "=f"(d[16]), "=f"(d[17]), "=f"(d[18]), "=f"(d[19]), "=f"(d[20]), "=f"(d[21]), "=f"(d[22]), "=f"(d[23]), "=f"(d[24]), "=f"(d[25]), "=f"(d[26]), "=f"(d[27]), "=f"(d[28]), "=f"(d[29]), "=f"(d[30]), "=f"(d[31])
    : "r"(a0), "r"(a1), "r"(a2), "r"(a3), "l"(desc));
}
template<> __device__ __forceinline__ void wgmma_rs_first<48,1>(float* d, uint32_t a0, uint32_t a1, uint32_t a2, uint32_t a3, uint64_t desc) {
  asm volatile("wgmma.mma_async.sync.aligned.m64n48k16.f32.bf16.bf16 {%0,%1,%2,%3,%4,%5,%6,%7,%8,%9,%10,%11,%12,%13,%14,%15,%16,%17,%18,%19,%20,%21,%22,%23}, {%24,%25,%26,%27}, %28, 0, 1, 1, 1;"
    : "=f"(d[0]), "=f"(d[1]), "=f"(d[2]), "=f"(d[3]), "=f"(d[4]), "=f"(d[5]), "=f"(d[6]), "=f"(d[7]), "=f"(d[8]), "=f"(d[9]), "=f"(d[10]), "=f"(d[11]), "=f"(d[12]), "=f"(d[13]), "=f"(d[14]), "=f"(d[15]), "=f"(d[16]), "=f"(d[17]), "=f"(d[18]), "=f"(d[19]), "=f"(d[20]), "=f"(d[21]), "=f"(d[22]), "=f"(d[23])
    : "r"(a0), "r"(a1), "r"(a2), "r"(a3), "l"(desc));
}

__device__ __forceinline__ void wg_fence()  { asm volatile("wgmma.fence.sync.aligned;" ::: "memory"); }
__device__ __forceinline__ void wg_commit() { asm volatile("wgmma.commit_group.sync.aligned;" ::: "memory"); }
template<int N> __device__ __forceinline__ void wg_wait() { asm volatile("wgmma.wait_group.sync.aligned %0;" :: "n"(N) : "memory"); }
template<int N> __device__ __forceinline__ void fence_regs(float* d) {
  #pragma unroll
  for (int i = 0; i < N; i++) asm volatile("" : "+f"(d[i]) :: "memory");
}
template<int N> __device__ __forceinline__ void redef(float* d) {
  #pragma unroll
  for (int i = 0; i < N; i++) { float y; asm volatile("mov.b32 %0, %1;" : "=f"(y) : "f"(d[i])); d[i] = y; }
}
__device__ __forceinline__ uint64_t mkdesc(uint32_t addr, uint32_t lbo, uint32_t sbo) {
  return (uint64_t)((addr & 0x3FFFF) >> 4) | ((uint64_t)(lbo >> 4) << 16) | ((uint64_t)(sbo >> 4) << 32);
}
__device__ __forceinline__ void bar_sync(int id, int n) { asm volatile("bar.sync %0, %1;" :: "r"(id), "r"(n) : "memory"); }
__device__ __forceinline__ uint32_t lds32(uint32_t a) { uint32_t v; asm volatile("ld.shared.u32 %0, [%1];" : "=r"(v) : "r"(a)); return v; }
__device__ __forceinline__ uint4 lds128(uint32_t a) { uint4 v; asm volatile("ld.shared.v4.u32 {%0,%1,%2,%3}, [%4];" : "=r"(v.x), "=r"(v.y), "=r"(v.z), "=r"(v.w) : "r"(a)); return v; }
__device__ __forceinline__ void bar_arrive(int id, int n) { asm volatile("bar.arrive %0, %1;" :: "r"(id), "r"(n) : "memory"); }
__device__ __forceinline__ void ldsm4t(uint32_t& r0, uint32_t& r1, uint32_t& r2, uint32_t& r3, uint32_t a) {
  asm volatile("ldmatrix.sync.aligned.m8n8.x4.trans.shared.b16 {%0,%1,%2,%3}, [%4];" : "=r"(r0), "=r"(r1), "=r"(r2), "=r"(r3) : "r"(a) : "memory");
}
__device__ __forceinline__ void stsm4(uint32_t a, uint32_t r0, uint32_t r1, uint32_t r2, uint32_t r3) {
  asm volatile("stmatrix.sync.aligned.m8n8.x4.shared.b16 [%0], {%1,%2,%3,%4};" :: "r"(a), "r"(r0), "r"(r1), "r"(r2), "r"(r3) : "memory");
}
__device__ __forceinline__ void stsm4t(uint32_t a, uint32_t r0, uint32_t r1, uint32_t r2, uint32_t r3) {
  asm volatile("stmatrix.sync.aligned.m8n8.x4.trans.shared.b16 [%0], {%1,%2,%3,%4};" :: "r"(a), "r"(r0), "r"(r1), "r"(r2), "r"(r3) : "memory");
}
__device__ __forceinline__ void sts16(uint32_t a, uint32_t v) { asm volatile("st.shared.u16 [%0], %1;" :: "r"(a), "r"(v) : "memory"); }
__device__ __forceinline__ void sts32(uint32_t a, uint32_t v) { asm volatile("st.shared.u32 [%0], %1;" :: "r"(a), "r"(v) : "memory"); }
__device__ __forceinline__ void sts128(uint32_t a, uint32_t x, uint32_t y, uint32_t z, uint32_t w) { asm volatile("st.shared.v4.u32 [%0], {%1,%2,%3,%4};" :: "r"(a), "r"(x), "r"(y), "r"(z), "r"(w) : "memory"); }
__device__ __forceinline__ uint32_t mapa(uint32_t a, uint32_t r) { uint32_t v; asm("mapa.shared::cluster.u32 %0, %1, %2;" : "=r"(v) : "r"(a), "r"(r)); return v; }
__device__ __forceinline__ float ex2(float x) { float y; asm("ex2.approx.ftz.f32 %0, %1;" : "=f"(y) : "f"(x)); return y; }
__device__ __forceinline__ float fsin(float x) { float y; asm("sin.approx.ftz.f32 %0, %1;" : "=f"(y) : "f"(x)); return y; }
__device__ __forceinline__ float fcos(float x) { float y; asm("cos.approx.ftz.f32 %0, %1;" : "=f"(y) : "f"(x)); return y; }
__device__ __forceinline__ float bf_lo(uint32_t w) { return __uint_as_float(w << 16); }
__device__ __forceinline__ float bf_hi(uint32_t w) { return __uint_as_float(w & 0xFFFF0000u); }
__device__ __forceinline__ uint32_t pk_h(float lo, float hi) { uint32_t d; asm("cvt.rn.f16x2.f32 %0, %1, %2;" : "=r"(d) : "f"(hi), "f"(lo)); return d; }
__device__ __forceinline__ uint32_t pk_bf(float lo, float hi) { uint32_t d; asm("cvt.rn.bf16x2.f32 %0, %1, %2;" : "=r"(d) : "f"(hi), "f"(lo)); return d; }
__device__ __forceinline__ uint32_t badd(uint32_t a, uint32_t b) { uint32_t d; asm("add.rn.bf16x2 %0, %1, %2;" : "=r"(d) : "r"(a), "r"(b)); return d; }
__device__ __forceinline__ uint32_t bmul(uint32_t a, uint32_t b) { uint32_t d; asm("mul.rn.bf16x2 %0, %1, %2;" : "=r"(d) : "r"(a), "r"(b)); return d; }
__device__ __forceinline__ uint32_t bsub(uint32_t a, uint32_t b) { uint32_t d; asm("sub.rn.bf16x2 %0, %1, %2;" : "=r"(d) : "r"(a), "r"(b)); return d; }
struct C2 { uint32_t r, i; };
__device__ __forceinline__ uint32_t hmul(uint32_t a, uint32_t b) { uint32_t d; asm("mul.rn.f16x2 %0, %1, %2;" : "=r"(d) : "r"(a), "r"(b)); return d; }
__device__ __forceinline__ uint32_t hfma(uint32_t a, uint32_t b, uint32_t c) { uint32_t d; asm("fma.rn.f16x2 %0, %1, %2, %3;" : "=r"(d) : "r"(a), "r"(b), "r"(c)); return d; }
__device__ __forceinline__ uint32_t hfnma(uint32_t a, uint32_t b, uint32_t c) {
  uint32_t d; asm("{.reg .b32 t; neg.f16x2 t, %1; fma.rn.f16x2 %0, t, %2, %3;}" : "=r"(d) : "r"(a), "r"(b), "r"(c)); return d;
}
__device__ __forceinline__ C2 cmul(C2 x, C2 z)  { C2 o; o.r = hfnma(x.i, z.i, hmul(x.r, z.r)); o.i = hfma(x.i, z.r, hmul(x.r, z.i)); return o; }
__device__ __forceinline__ C2 cmulc(C2 x, C2 z) { C2 o; o.r = hfma(x.i, z.i, hmul(x.r, z.r)); o.i = hfnma(x.r, z.i, hmul(x.i, z.r)); return o; }
__device__ __forceinline__ void csq(float& r, float& i) { float t = i * i; float n = fmaf(r, r, -t); i = __uint_as_float(__float_as_uint(r * i) + 0x00800000u); r = n; }

#define TICK(k)

__device__ __forceinline__ uint32_t cpy(uint32_t x) { uint32_t y; asm volatile("mov.b32 %0, %1;" : "=r"(y) : "r"(x)); return y; }
__device__ __forceinline__ void keep(uint32_t& x) { asm volatile("" : "+r"(x)); }
__device__ __forceinline__ int tid_now() { int t; asm volatile("mov.u32 %0, %%tid.x;" : "=r"(t)); return t; }
struct Frag { uint32_t a0, a1, a2, a3; };
template<int N> __device__ __forceinline__ void raw_load(uint32_t* raw, uint32_t base, int p) {
  #pragma unroll
  for (int i = 0; i < N; i++) raw[i] = lds32(base - 16 * (p - 1 + i));
}
__device__ __forceinline__ Frag mkfrag(const uint32_t* r, bool first) { Frag f; f.a0 = r[1]; f.a1 = r[2]; f.a2 = first ? r[0] : cpy(r[0]); f.a3 = cpy(r[1]); return f; }
template<int S> __device__ __forceinline__ void dense_step(float* acc, const Frag& f, uint64_t d0) {
  constexpr int kk = S & 1, m = (S + 1) >> 1;
  constexpr int N = (m < 8) ? 64 : 56;
  if constexpr (S == -1) wgmma_rs_first<64, 0>(acc, f.a0, f.a1, f.a2, f.a3, d0 + (uint64_t)((2 * kk * U1_PLANE + m * 16) >> 4));
  else wgmma_rs<N, 0>(acc, f.a0, f.a1, f.a2, f.a3, d0 + (uint64_t)((2 * kk * U1_PLANE + m * 16) >> 4));
}
template<int S0, int NS> __device__ __forceinline__ void dense_load(uint32_t* raw, uint32_t base) {
  #pragma unroll
  for (int i = 1; i <= 2 * NS; i++) raw[i] = lds32(base - 16 * (2 * S0 - 1 + i));
}
template<int S0, int NS> __device__ __forceinline__ void dense_group(float* acc, uint32_t* raw, uint64_t d0) {
  Frag f[4];
  #pragma unroll
  for (int i = 0; i < NS; i++) f[i] = mkfrag(raw + 2 * i, i == 0);
  raw[0] = cpy(raw[2 * NS]);
  wg_fence();
  dense_step<S0>(acc, f[0], d0); dense_step<S0 + 1>(acc, f[1], d0); dense_step<S0 + 2>(acc, f[2], d0);
  if constexpr (NS > 3) dense_step<S0 + 3>(acc, f[3], d0);
  wg_commit();
}
template<int S, int N, bool FIRST = false> __device__ __forceinline__ void far_step(float* acc, const Frag& f, uint64_t d0) {
  constexpr int fl = (S >= 0) ? (S / 2) : -((1 - S) / 2);
  if constexpr (FIRST) wgmma_rs_first<N, 1>(acc, f.a0, f.a1, f.a2, f.a3, d0 + (uint64_t)(((-fl) * 512 + (S & 1) * 256) >> 4));
  else wgmma_rs<N, 1>(acc, f.a0, f.a1, f.a2, f.a3, d0 + (uint64_t)(((-fl) * 512 + (S & 1) * 256) >> 4));
}
template<int S, int N, bool FIRST = false> __device__ __forceinline__ void s2_group(float* acc, const uint32_t* raw, uint64_t da, uint64_t db) {
  const Frag f0 = mkfrag(raw, true), f1 = mkfrag(raw + 2, false), f2 = mkfrag(raw + 5, true), f3 = mkfrag(raw + 7, false);
  wg_fence();
  far_step<S, N, FIRST>(acc, f0, da); far_step<S - 1, N>(acc, f1, da); far_step<S, N>(acc, f2, db); far_step<S - 1, N>(acc, f3, db);
  wg_commit();
}
template<int S, int N> __device__ __forceinline__ void s3_group(float* acc, const uint32_t* raw, uint32_t m, uint64_t da, uint64_t db) {
  uint32_t x[5], y[5];
  #pragma unroll
  for (int i = 0; i < 5; i++) {
    asm volatile("and.b32 %0, %1, %2;" : "=r"(x[i]) : "r"(raw[i]), "r"(m)); asm volatile("and.b32 %0, %1, %2;" : "=r"(y[i]) : "r"(raw[i]), "r"(~m));
  }
  const Frag f0 = mkfrag(x, true), f1 = mkfrag(x + 2, false), f2 = mkfrag(y, true), f3 = mkfrag(y + 2, false);
  wg_fence();
  far_step<S, N>(acc, f0, da); far_step<S - 1, N>(acc, f1, da); far_step<S, N>(acc, f2, db); far_step<S - 1, N>(acc, f3, db);
  wg_commit();
}
__device__ __forceinline__ void mma16816bf(float* c, uint32_t a0, uint32_t a1, uint32_t a2, uint32_t a3, uint32_t b0, uint32_t b1) {
  asm volatile("mma.sync.aligned.m16n8k16.row.col.f32.bf16.bf16.f32 {%0,%1,%2,%3}, {%4,%5,%6,%7}, {%8,%9}, {%0,%1,%2,%3};"
    : "+f"(c[0]), "+f"(c[1]), "+f"(c[2]), "+f"(c[3]) : "r"(a0), "r"(a1), "r"(a2), "r"(a3), "r"(b0), "r"(b1));
}
__device__ __forceinline__ void mbar_wait(uint32_t bar, uint32_t parity) {
  uint32_t ok = 0; int it = 0;
  do {
    asm volatile("{.reg .pred p; mbarrier.try_wait.parity.shared::cta.b64 p, [%1], %2; selp.u32 %0, 1, 0, p;}" : "=r"(ok) : "r"(bar), "r"(parity) : "memory");
  } while (!ok && ++it < (1 << 22));
}
__device__ __forceinline__ void cexp2(float& r, float& i, float e, float x) {
  const float k = __fadd_rn(fmaf(x, 0.15915494309189535f, 12582912.f), -12582912.f);
  const float m = ex2(e), a = fmaf(k, -6.283185307179586f, x);
  r = m * fcos(a); i = m * fsin(a);
}
__device__ __forceinline__ void mma16816(float* c, uint32_t a0, uint32_t a1, uint32_t a2, uint32_t a3, uint32_t b0, uint32_t b1) {
  asm("mma.sync.aligned.m16n8k16.row.col.f32.f16.f16.f32 {%0,%1,%2,%3}, {%4,%5,%6,%7}, {%8,%9}, {%0,%1,%2,%3};"
    : "+f"(c[0]), "+f"(c[1]), "+f"(c[2]), "+f"(c[3]) : "r"(a0), "r"(a1), "r"(a2), "r"(a3), "r"(b0), "r"(b1));
}
__device__ __forceinline__ void sts32p(bool p, uint32_t a, uint32_t v) {
  asm volatile("{.reg .pred p; setp.ne.u32 p, %2, 0; @p st.shared.u32 [%0], %1;}" :: "r"(a), "r"(v), "r"((uint32_t)p) : "memory");
}

__device__ __forceinline__ void load_E(uint32_t* E, uint32_t bU, int tau) {
  #pragma unroll
  for (int k = 0; k < 3; k++) {
    const int t = tau - 2 + k;
    const uint4 e = lds128(bU + (t & 3) * U1_PLANE + (63 - (t >> 2)) * 16);
    E[4 * k] = e.x; E[4 * k + 1] = e.y; E[4 * k + 2] = e.z; E[4 * k + 3] = e.w;
  }
}
template<bool FULL> __device__ __forceinline__ void build_V(const uint32_t* E, uint32_t bV, int tau) {
  uint32_t O[11], Q[11], R[10], V3[11], V5[10];
  #pragma unroll
  for (int n = FULL ? 3 : 4; n <= 10; n++) { O[n] = __byte_perm(E[n - 1], E[n], 0x5432); Q[n] = badd(O[n], E[n - 1]); }
  #pragma unroll
  for (int n = FULL ? 4 : 5; n <= (FULL ? 9 : 8); n++) R[n] = badd(Q[n], Q[n - 1]);
  #pragma unroll
  for (int n = FULL ? 4 : 7; n <= 10; n++) V3[n] = badd(Q[n], O[n - 1]);
  #pragma unroll
  for (int n = 5; n <= (FULL ? 9 : 8); n++) V5[n] = badd(E[n], R[n]);
  const uint32_t o6 = bV + (5 - (tau >> 5)) * 512 + (tau & 31) * 16;
  sts128(o6 + V3_OFF, V3[7], V3[8], V3[9], V3[10]);
  sts128(o6 + V5_OFF, V5[5], V5[6], V5[7], V5[8]);
  if (FULL) {
    sts128(o6 - 1024 + V7_OFF, badd(R[6], V3[4]), badd(R[7], V3[5]), badd(R[8], V3[6]), badd(R[9], V3[7]));
    sts128(o6 - 1024 + V9_OFF, badd(V5[6], R[4]), badd(V5[7], R[5]), badd(V5[8], R[6]), badd(V5[9], R[7]));
    sts128(o6 - 1024 + V2_OFF, Q[7], Q[8], Q[9], Q[10]);
  }
}

__global__ void __cluster_dims__(2, 1, 1) __launch_bounds__(512, 1)
s4d_kernel(const __grid_constant__ Params P, const __grid_constant__ CUtensorMap tmU) {
  extern __shared__ __align__(256) uint8_t smem[];
  const int pbr = (threadIdx.x >> 6) & 1, pch = blockIdx.x * 4 + (threadIdx.x >> 7), pidx = pch * 64 + (threadIdx.x & 63);
  const uint32_t wLA = __ldg((pbr ? P.logA[1] : P.logA[0]) + pidx), wAI = __ldg((pbr ? P.Aim[1] : P.Aim[0]) + pidx);
  const uint32_t wDT = __ldg((pbr ? P.logdt[1] : P.logdt[0]) + pch);
  const uint32_t* pCR = pbr ? P.Cre[1] : P.Cre[0];
  const uint32_t* pCI = pbr ? P.Cim[1] : P.Cim[0];
  const uint32_t wCR = __ldg(pCR + pidx), wCI = __ldg(pCI + pidx), wCR2 = __ldg(pCR + (pidx ^ 32)), wCI2 = __ldg(pCI + (pidx ^ 32));
  const uint32_t wDS = __ldg((pbr ? P.Dsk[1] : P.Dsk[0]) + pch);
  unsigned epoch;
  asm volatile("ld.relaxed.gpu.global.u32 %0, [%1];" : "=r"(epoch) : "l"(P.epoch) : "memory");
  const uint32_t sb = (uint32_t)__cvta_generic_to_shared(smem);
  const int tid = threadIdx.x, lane = tid & 31, wi = __shfl_sync(0xFFFFFFFFu, tid >> 5, 0), wg = wi >> 2, wq = wi & 3;
  const int g = lane >> 2, q = lane & 3, br = wq >> 1, hh = wq & 1;
  const int rank = blockIdx.x & 1, clus = blockIdx.x >> 1;
  const uint32_t barU = sb + OFF_MISC, barY = sb + OFF_MISC + 8, junk = sb + OFF_MISC + 128;
  const bool late = wg >= 2;

  const uint32_t sT = sb + OFF_T + (wg * 2 + br) * T_BR;
  const uint32_t sU = sb + OFF_U1 + wg * U1_CH;
  const uint32_t sW = sb + OFF_W + wg * W_WG;
  const uint32_t sR = sW + wq * R_WARP;
  const uint32_t we = sR + lane * 4, wo = sR + (lane ^ 16) * 4;
  {
    #pragma unroll
    for (int k = 0; k < 4; k++) sts128(sT + hh * CP + lane * 16 + k * 512, 0, 0, 0, 0);
    sts32p(lane < 16, sT + hh * CP + 2048 + lane * 4, 0);
    sts128((tid < 160) ? sb + OFF_U1 + (tid & 3) * U1_CH + ((tid >> 2) & 3) * U1_PLANE + (64 + (tid >> 4)) * 16 : junk + (lane & 7) * 16, 0, 0, 0, 0);
    sts32(we + 48 * 128, 0x3C003C00u); sts32(we + 56 * 128, 0u);
  }
  const int j0 = 16 * hh + g;
  const bool lo = q < 2, fix = (hh == 0) && (g == 0) && !(q & 1);
  const uint32_t jk = sR + 2560 + lane * 4;
  const uint32_t c0 = sT + T_D + 2 * (303 - 8 * j0 - 4 * q), p3 = sT + T_P3 + 2 * (159 - j0 - 32 * q);
  uint32_t tb0 = sT + T_D + 2 * (558 - 8 * j0 - 2 * q);
  uint32_t tcl = lo ? c0 : jk + 2, tph = lo ? jk : p3, tpa = lo ? sT + T_PS + 2 * (128 - 64 * q - j0) : jk;
  uint32_t tu3 = lo ? c0 + 2 - 128 : p3 + (T_P5 - T_P3) + 2 - 16, tu2 = lo ? c0 - 4 : p3, tu4 = lo ? c0 - 4 - 128 : p3 - 16;
  uint32_t tu1 = fix ? jk : tu3 + (lo ? 128 : 16), tcf = fix ? jk + 2 : tcl, tphf = fix ? jk : tph, tpaf = fix ? jk : tpa;
  const int rw = (lane & 7) - 4 * rank;
  uint32_t xdst = sb + OFF_U1 + (lane >> 3) * U1_PLANE + (63 - 8 * (wi & 7)) * 16 + rw * U1_CH;
  if ((unsigned)rw >= 4u) xdst = junk + 128 + (xdst & 127u);
  uint32_t xsrc = sb + OFF_RAW + ((wi & 7) * 256 + lane) * 16;
  const int x0 = g - 2 * q + 16 * hh;
  uint32_t gL = sT + ((g & 1) ? 0 : CP + 2) - 2 * x0;
  keep(tb0); keep(tcl); keep(tph); keep(tpa); keep(tu1); keep(tu2); keep(tu3); keep(tu4); keep(tcf); keep(tphf); keep(tpaf); keep(xdst); keep(xsrc); keep(gL);

  asm volatile("fence.proxy.async.shared::cta;" ::: "memory");
  __syncwarp();
  if (lane == 0 && late) {
    asm volatile("cp.async.bulk.global.shared::cta.bulk_group [%0], [%1], 2048;" :: "l"(P.out + (size_t)(blockIdx.x * 16 + (wi & 7) * 2) * 64), "r"(sT + hh * CP) : "memory");
    asm volatile("cp.async.bulk.commit_group;" ::: "memory");
  }
  if (tid == 480) {
    asm volatile("prefetch.tensormap [%0];" :: "l"(&tmU) : "memory");
    asm volatile("mbarrier.init.shared::cta.b64 [%0], 1;" :: "r"(barU) : "memory");
    asm volatile("mbarrier.init.shared::cta.b64 [%0], 5;" :: "r"(barY) : "memory");
    asm volatile("mbarrier.init.shared::cta.b64 [%0], 5;" :: "r"(barY + 8) : "memory");
    asm volatile("mbarrier.init.shared::cta.b64 [%0], 5;" :: "r"(barY + 16) : "memory");
    asm volatile("mbarrier.arrive.expect_tx.shared::cta.b64 _, [%0], %1;" :: "r"(barU), "r"(32768) : "memory");
    asm volatile("mbarrier.arrive.expect_tx.shared::cta.b64 _, [%0], %1;" :: "r"(barY), "r"(4 * Y_OWN) : "memory");
    asm volatile("mbarrier.arrive.expect_tx.shared::cta.b64 _, [%0], %1;" :: "r"(barY + 8), "r"(4 * Y_BLK) : "memory");
    asm volatile("mbarrier.arrive.expect_tx.shared::cta.b64 _, [%0], %1;" :: "r"(barY + 16), "r"(8 * Y_BLK) : "memory");
    asm volatile("fence.mbarrier_init.release.cluster;" ::: "memory");
  }
  __syncwarp();
  asm volatile("barrier.cluster.arrive.relaxed.aligned;" ::: "memory");
  if (wi == 15) {
    asm volatile("barrier.cluster.wait.aligned;" ::: "memory");
    if (lane == 0) {
      #pragma unroll
      for (int k = 0; k < 4; k++)
        asm volatile("cp.async.bulk.tensor.2d.shared::cluster.global.mbarrier::complete_tx::bytes.multicast::cluster [%0], [%1, {%3, %4}], [%2], %5;"
          :: "r"(sb + OFF_RAW + (rank * 1024 + k * 256) * 16 TMADEP), "l"(&tmU), "r"(barU), "r"(clus * 8), "r"(rank * 1024 + k * 256), "h"((unsigned short)3) : "memory");
    }
    __syncwarp();
  }

  const float dt = bf_lo(pk_bf(ex2(bf_lo(wDT) * 1.4426950408889634f), 0.f));
  float csc, tsc;
  {
    uint32_t m = __vmaxu2(__vmaxu2(wCR & 0x7FFF7FFFu, wCI & 0x7FFF7FFFu), __vmaxu2(wCR2 & 0x7FFF7FFFu, wCI2 & 0x7FFF7FFFu));
    m = max(m & 0xFFFFu, m >> 16);
    m = __reduce_max_sync(0xFFFFFFFFu, m);
    int k = 140 - (int)(m >> 7);
    k = min(max(k, -126), 126);
    csc = __uint_as_float((uint32_t)(k + 127) << 23);
    tsc = 2.0f * dt * __uint_as_float((uint32_t)(127 - k) << 23);
  }
  uint4 gx0, gx1, gx2, gx3, gw0, gw1;
  if (late) {
    const size_t grow = (size_t)(blockIdx.x * 16 + (wi & 7) * 2) * 64 + lane + (csc == 0.f ? 1 : 0);
    gx0 = __ldg(P.u + grow); gx1 = __ldg(P.u + grow + 32); gx2 = __ldg(P.u + grow + 64); gx3 = __ldg(P.u + grow + 96);
    gw0 = __ldg(P.gw + lane); gw1 = __ldg(P.gw + 32 + lane);
  }
  TICK(0);
  {
    const uint32_t Ab = pk_bf(ex2(bf_lo(wLA) * 1.4426950408889634f), ex2(bf_hi(wLA) * 1.4426950408889634f));
    const float ndt = dt * -1.4426950408889634f;
    const float ea = bf_lo(Ab) * ndt, eb = bf_hi(Ab) * ndt, ta = bf_lo(wAI) * dt, tb = bf_hi(wAI) * dt;
    float ra, ia, rb, ib, sa, ja, sb2, jb;
    cexp2(ra, ia, ea, ta); cexp2(rb, ib, eb, tb);
    cexp2(sa, ja, ea * 64.f, ta * 64.f); cexp2(sb2, jb, eb * 64.f, tb * 64.f);
#define PK1 C2{pk_h(ra, rb), pk_h(ia, ib)}
#define PK6 C2{pk_h(sa, sb2), pk_h(ja, jb)}
#define SQ1 csq(ra, ia); csq(rb, ib);
#define SQ6 csq(sa, ja); csq(sb2, jb);
#define PUT(T, G, V) { sts32(((G) & 1 ? wo : we) + ((T) * 16 + (G)) * 128, (V).r); sts32(((G) & 1 ? wo : we) + ((T) * 16 + 8 + (G)) * 128, (V).i); }
    C2 H0[8], X[8], H1[8], H2[5];
    H0[0] = C2{pk_h(bf_lo(wCR) * csc, bf_hi(wCR) * csc), pk_h(bf_lo(wCI) * -csc, bf_hi(wCI) * -csc)}; PUT(0, 0, H0[0])
    const C2 Z = PK6;
    sts32(we + 64 * 128, Z.r); sts32(we + 65 * 128, Z.i);
    const C2 m1 = PK1; H0[1] = cmulc(H0[0], m1); PUT(0, 1, H0[1])
    SQ1 SQ6 const C2 m2 = PK1;
    H0[2] = cmulc(H0[0], m2); PUT(0, 2, H0[2]) H0[3] = cmulc(H0[1], m2); PUT(0, 3, H0[3])
    SQ1 SQ6 const C2 m4 = PK1, m256 = PK6;
    H0[4] = cmulc(H0[0], m4); PUT(0, 4, H0[4]) H0[5] = cmulc(H0[1], m4); PUT(0, 5, H0[5])
    H0[6] = cmulc(H0[2], m4); PUT(0, 6, H0[6]) H0[7] = cmulc(H0[3], m4); PUT(0, 7, H0[7])
    SQ1 SQ6 X[1] = PK1; PUT(3, 1, X[1]) const C2 m512 = PK6;
    H1[0] = cmulc(H0[0], m256); PUT(1, 0, H1[0]) H1[1] = cmulc(H0[2], m256); PUT(1, 1, H1[1])
    H1[2] = cmulc(H0[4], m256); PUT(1, 2, H1[2]) H1[3] = cmulc(H0[6], m256); PUT(1, 3, H1[3])
    SQ1 SQ6 X[2] = PK1; PUT(3, 2, X[2]) const C2 m1k = PK6;
    H1[4] = cmulc(H0[0], m512); PUT(1, 4, H1[4]) H1[5] = cmulc(H0[4], m512); PUT(1, 5, H1[5])
    H1[6] = cmulc(H1[0], m512); PUT(1, 6, H1[6]) H1[7] = cmulc(H1[2], m512); PUT(1, 7, H1[7])
    SQ1 X[4] = PK1; PUT(3, 4, X[4])
    X[3] = cmul(X[2], X[1]); PUT(3, 3, X[3])
    H2[0] = cmulc(H0[0], m1k); PUT(2, 0, H2[0]) H2[1] = cmulc(H1[0], m1k); PUT(2, 1, H2[1])
    H2[2] = cmulc(H1[4], m1k); PUT(2, 2, H2[2]) H2[3] = cmulc(H1[6], m1k); PUT(2, 3, H2[3])
    X[5] = cmul(X[4], X[1]); PUT(3, 5, X[5]) X[6] = cmul(X[4], X[2]); PUT(3, 6, X[6])
    H2[4] = cmulc(H2[0], m1k); PUT(2, 4, H2[4]) X[7] = cmul(X[6], X[1]); PUT(3, 7, X[7])
#undef PUT
#undef PK1
#undef PK6
#undef SQ1
#undef SQ6
  }
  if (late) {
    float sm[4] = {0.f, 0.f, 0.f, 0.f};
    const uint32_t one = 0x3F803F80u;
#define GMMA(A, B, W) mma16816bf(sm, bmul(A.x, W.x), bmul(B.x, W.x), bmul(A.y, W.y), bmul(B.y, W.y), one, one); \
                      mma16816bf(sm, bmul(A.z, W.z), bmul(B.z, W.z), bmul(A.w, W.w), bmul(B.w, W.w), one, one);
    GMMA(gx0, gx2, gw0) GMMA(gx1, gx3, gw1)
#undef GMMA
    float s = (q & 1) ? sm[2] : sm[0];
    s += __shfl_xor_sync(0xFFFFFFFFu, s, 4); s += __shfl_xor_sync(0xFFFFFFFFu, s, 8); s += __shfl_xor_sync(0xFFFFFFFFu, s, 16);
    s = bf_lo(pk_bf(s, 0.f));
    const float gv = __fdividef(1.0f, 1.0f + ex2(s * -1.4426950408889634f));
    const uint32_t gpub = ((epoch + 1) << 16) | (pk_bf(gv, 0.f) & 0xFFFFu);
    if (lane == 0) asm volatile("cp.async.bulk.wait_group 0;" ::: "memory");
    __syncwarp();
    if (lane < 2) asm volatile("st.relaxed.gpu.global.u32 [%0], %1;" :: "l"(P.gate + blockIdx.x * 16 + (wi & 7) * 2 + lane), "r"(gpub) : "memory");
    TICK(5);
  }
  if (wi != 15) asm volatile("barrier.cluster.wait.aligned;" ::: "memory");
  __syncwarp();
  TICK(1);
  float cD[2][3][4];
  #pragma unroll
  for (int i = 0; i < 2; i++)
    #pragma unroll
    for (int j = 0; j < 3; j++)
      #pragma unroll
      for (int k = 0; k < 4; k++) cD[i][j][k] = __uint_as_float(cpy(0u));
  {
    #pragma unroll
    for (int h2 = 0; h2 < 2; h2++) {
      const uint32_t r0 = sR + g * 128 + 16 * ((q + 4 * h2) ^ (4 * (g & 1))), zb = sR + 64 * 128 + 16 * (q + 4 * h2);
      const uint4 Xr = lds128(r0 + 48 * 128), Xi = lds128(r0 + 56 * 128), Zr = lds128(zb), Zi = lds128(zb + 128);
      const uint4 H0r = lds128(r0), H0i = lds128(r0 + 8 * 128), H1r = lds128(r0 + 16 * 128), H1i = lds128(r0 + 24 * 128);
      const uint4 H2r = lds128(r0 + 32 * 128), H2i = lds128(r0 + 40 * 128);
#define KSTEP(E, F) { \
      const C2 za = C2{Zr.E, Zi.E}, zc = C2{Zr.F, Zi.F}, a0 = C2{Xr.E, Xi.E}, c0 = C2{Xr.F, Xi.F}; \
      const C2 a1 = cmul(a0, za), c1 = cmul(c0, zc), a2 = cmul(a1, za), c2 = cmul(c1, zc), a3 = cmul(a2, za), c3 = cmul(c2, zc); \
      mma16816(cD[0][0], a0.r, a1.r, c0.r, c1.r, H0r.E, H0r.F); mma16816(cD[0][1], a0.r, a1.r, c0.r, c1.r, H1r.E, H1r.F); \
      mma16816(cD[0][2], a0.r, a1.r, c0.r, c1.r, H2r.E, H2r.F); \
      mma16816(cD[0][0], a0.i, a1.i, c0.i, c1.i, H0i.E, H0i.F); mma16816(cD[0][1], a0.i, a1.i, c0.i, c1.i, H1i.E, H1i.F); \
      mma16816(cD[0][2], a0.i, a1.i, c0.i, c1.i, H2i.E, H2i.F); \
      mma16816(cD[1][0], a2.r, a3.r, c2.r, c3.r, H0r.E, H0r.F); mma16816(cD[1][1], a2.r, a3.r, c2.r, c3.r, H1r.E, H1r.F); \
      mma16816(cD[1][2], a2.r, a3.r, c2.r, c3.r, H2r.E, H2r.F); \
      mma16816(cD[1][0], a2.i, a3.i, c2.i, c3.i, H0i.E, H0i.F); mma16816(cD[1][1], a2.i, a3.i, c2.i, c3.i, H1i.E, H1i.F); \
      mma16816(cD[1][2], a2.i, a3.i, c2.i, c3.i, H2i.E, H2i.F); }
      KSTEP(x, y) KSTEP(z, w)
#undef KSTEP
    }
  }
  __syncwarp();
  TICK(2);
  float v[12];
  {
    const uint32_t sO = sW + (wq ^ 1) * R_WARP + lane * 16, sS = sR + lane * 16;
#define XCH(SND, KEEP) \
    _Pragma("unroll") for (int k = 0; k < 3; k++) sts128(sS + k * 512, __float_as_uint(cD[SND][k][0]), __float_as_uint(cD[SND][k][1]), __float_as_uint(cD[SND][k][2]), __float_as_uint(cD[SND][k][3])); \
    bar_sync(1 + wg * 2 + br, 64); \
    _Pragma("unroll") for (int k = 0; k < 3; k++) { const uint4 o = lds128(sO + k * 512); \
      v[4 * k + 0] = (cD[KEEP][k][0] + __uint_as_float(o.x)) * tsc; v[4 * k + 1] = (cD[KEEP][k][1] + __uint_as_float(o.y)) * tsc; \
      v[4 * k + 2] = (cD[KEEP][k][2] + __uint_as_float(o.z)) * tsc; v[4 * k + 3] = (cD[KEEP][k][3] + __uint_as_float(o.w)) * tsc; }
    if (hh) { XCH(0, 1) } else { XCH(1, 0) }
#undef XCH
  }
  uint32_t w1f = 0, w2f = 0;
  {
    if (hh == 0 && lane == 0) v[0] += bf_lo(wDS);
    #pragma unroll
    for (int a = 0; a < 2; a++) {
      const uint32_t w0 = pk_bf(v[2 * a + 1], v[2 * a]);
      sts32(tb0 - 128 * a, w0);
      sts16(tb0 - 128 * a + CP + 4, w0 >> 16);
      sts16(tb0 - 128 * a + CP + 2, w0);
      const uint32_t w1 = pk_bf(v[4 + 2 * a], v[5 + 2 * a]);
      const uint32_t aa = __byte_perm(w1, 0, 0x1010), ba = __byte_perm(w1, 0, 0x1032);
      sts16(a ? tu3 : tu1, w1);
      sts16(a ? tu4 : tu2, ba);
      const uint32_t w2 = pk_bf(v[8 + 2 * a], v[9 + 2 * a]);
      sts32(tcl - 128 * a - 2, aa);
      sts32((a ? tcl : tcf) - 128 * a + CP + 2, aa);
      sts32(tcl - 128 * a + CP - 2, ba);
      sts16((a ? tph : tphf) - 16 * a + T_P5 - T_P3 + CP + 4, w1);
      sts16(tph - 16 * a + CP + 2, ba);
      sts16((a ? tpa : tpaf) - 16 * a, w2); sts16((a ? tpa : tpaf) - 16 * a + CP + 2, w2);
      sts16(tpa - 16 * a - 64, w2 >> 16); sts16(tpa - 16 * a - 64 + CP + 2, w2 >> 16);
      if (a == 0) { w1f = aa; w2f = w2; }
    }
    if (fix) {
      if (q == 0) {
        sts16(sT + T_D + CP + 2 * (560 - 256), w1f);
        sts16(sT + T_P5 + 64, w2f); sts16(sT + T_P5 + CP + 66, w2f);
      } else {
        sts32(sT + T_D + 92, w1f); sts16(sT + T_D + 96, w1f); sts16(sT + T_D + 90, w1f);
        sts32(sT + T_D + CP + 96, w1f); sts32(sT + T_D + CP + 92, w1f);
        sts16(sT + T_PS, w2f); sts16(sT + T_PS + CP + 2, w2f);
      }
    }
  }
  TICK(3);

  if (!late) {
    mbar_wait(barU, 0);
    TICK(4);
    uint32_t r[8][4];
    #pragma unroll
    for (int k = 0; k < 8; k++) ldsm4t(r[k][0], r[k][1], r[k][2], r[k][3], xsrc + k * 512);
    #pragma unroll
    for (int k = 0; k < 8; k++) stsm4(xdst - 16 * k, r[k][0], r[k][1], r[k][2], r[k][3]);
    asm volatile("fence.proxy.async.shared::cta;" ::: "memory");
    bar_arrive(15, 512);
    bar_sync(14, 256);
  } else {
    bar_sync(15, 512);
  }
  asm volatile("barrier.cluster.arrive.relaxed.aligned;" ::: "memory");
  TICK(6);
  const uint32_t g3 = gL + T_P3 + 190, g5 = gL + T_P5 + 190, gS = gL + T_PS + 254, gD = gL + T_D + 1118;
  const uint32_t sV = sW;
  const int role = (wq + wg) & 3;
#define PK4(A, B) pk_bf(A[4 * (B)], A[4 * (B) + 1]), pk_bf(A[4 * (B) + 2], A[4 * (B) + 3]), pk_bf(A[4 * (B) + 4], A[4 * (B) + 5]), pk_bf(A[4 * (B) + 6], A[4 * (B) + 7])
#define SEND(SRC, STRIDE, DST, BYTES, BAR) \
  asm volatile("fence.proxy.async.shared::cta;" ::: "memory"); \
  bar_sync(9 + wg, 128); \
  if ((tid_now() & 127) == 0) { \
    asm volatile("cp.async.bulk.shared::cluster.shared::cta.mbarrier::complete_tx::bytes [%0], [%1], %2, [%3];" \
      :: "r"(mapa(sb + (DST), rank ^ 1)), "r"(sW + (SRC) + (rank ^ 1) * (STRIDE)), "r"(BYTES), "r"(mapa(BAR, rank ^ 1)) : "memory"); \
    asm volatile("mbarrier.arrive.shared::cta.b64 _, [%0];" :: "r"(BAR) : "memory"); \
  }
#define TAILS { const uint32_t z = sV + lane * 16 + (role & 1) * V5_OFF, y = sV + lane * 16 + V7_OFF + (role & 1) * (V9_OFF - V7_OFF); \
      sts128(z + 3072, 0, 0, 0, 0); sts128(y + 2048, 0, 0, 0, 0); sts128(y + 2560, 0, 0, 0, 0); }

  float acc1[32], acc2[24];
  uint32_t raw[10];
  const uint64_t dU = mkdesc(sU, U1_PLANE, 128);
  raw_load<9>(raw, gD, -2);
  {
    uint32_t E[12], E2[12];
    load_E(E, sU, role * 32 + lane);
    load_E(E2, sU, 128 + (role & 1) * 32 + lane);
    build_V<true>(E, sV, role * 32 + lane);
    if (role < 2) build_V<false>(E2, sV, 128 + role * 32 + lane); else TAILS
  }
  dense_group<-1, 4>(acc1, raw, dU);
  dense_load<3, 4>(raw, gD);
  dense_group<3, 4>(acc1, raw, dU);
  dense_load<7, 4>(raw, gD);
  wg_wait<1>();
  dense_group<7, 4>(acc1, raw, dU);
  dense_load<11, 4>(raw, gD);
  wg_wait<1>();
  dense_group<11, 4>(acc1, raw, dU);
  dense_load<15, 4>(raw, gD);
  asm volatile("fence.proxy.async.shared::cta;" ::: "memory");
  wg_wait<0>();
  redef<28>(acc1);
  dense_group<15, 4>(acc1, raw, dU);
  dense_load<19, 4>(raw, gD);
  dense_group<19, 4>(acc1, raw, dU);
  dense_load<23, 4>(raw, gD);
  bar_sync(9 + wg, 128);
  wg_wait<1>();
  dense_group<23, 4>(acc1, raw, dU);
  dense_load<27, 4>(raw, gD);
  unsigned long long gv;
  asm volatile("ld.relaxed.gpu.global.b64 %0, [%1];" : "=l"(gv) : "l"(P.gate + wg * 512 + rank * 256 + 2 * (tid_now() & 127)) : "memory");
  asm volatile("barrier.cluster.wait.aligned;" ::: "memory");
  wg_wait<1>();
  dense_group<27, 4>(acc1, raw, dU);
  dense_load<31, 3>(raw, gD);
  wg_wait<1>();
  dense_group<31, 3>(acc1, raw, dU);

  const uint64_t d3 = mkdesc(sV + V3_OFF, 128, 512), d5 = mkdesc(sV + V5_OFF, 128, 512);
  const uint64_t d7 = mkdesc(sV + V7_OFF, 128, 512), d9 = mkdesc(sV + V9_OFF, 128, 512), d2 = mkdesc(sV + V2_OFF, 128, 512);
  const uint32_t m7 = (g & 1) ? 0xFFFF0000u : 0x0000FFFFu;
  raw_load<5>(raw, g3, -2); raw_load<5>(raw + 5, g5, -2);
  wg_wait<1>();
  s2_group<1, 48, true>(acc2, raw, d3, d5);
  raw_load<5>(raw, g3, 2); raw_load<5>(raw + 5, g5, 2);
  wg_wait<1>();
  fence_regs<32>(acc1);
  TICK(7);
  s2_group<-1, 48>(acc2, raw, d3, d5);
  raw_load<5>(raw, g3, 6); raw_load<5>(raw + 5, g5, 6);
  {
    const int ln = tid_now(), mat = (ln >> 3) & 3, r8 = ln & 7;
    const uint32_t sY = sW + Y_OFF + (1 - (mat >> 1)) * Y_OWN + (br * 4 + 2 * hh + (mat & 1)) * Y_PLANE + r8 * 16;
    stsm4t(sY + 3 * Y_BLK, PK4(acc1, 0)); stsm4t(sY + 2 * Y_BLK, PK4(acc1, 2));
    stsm4t(sY + Y_BLK, PK4(acc1, 4)); stsm4t(sY, PK4(acc1, 6));
  }
  SEND(Y_OFF, Y_OWN, OFF_RAW + wg * Y_OWN, Y_OWN, barY)
  uint32_t sF;
  {
    const int ln = tid_now(), mat = (ln >> 3) & 3, r8 = ln & 7;
    sF = sW + F_OFF + (1 - (mat >> 1)) * F_OWN + (br * 4 + (r8 & 3)) * Y_PLANE + (7 - 4 * hh - 2 * (mat & 1) - (r8 >> 2)) * 16;
  }
  wg_wait<0>();
  fence_regs<8>(acc2 + 16);
  redef<16>(acc2);
  s2_group<-3, 32>(acc2, raw, d3, d5);
  raw_load<5>(raw, gS, -2);
  raw[5] = lds32(sT + T_P5 + 64);
  s3_group<1, 32>(acc2, raw, m7, d7, d9);
  {
    const int ln = tid_now() & 31, df = (ln >> 2) - 2 * (ln & 3);
    const uint32_t b = raw[5] & 0xFFFFu, dg = (df == 0) ? b : ((df == 1) ? (b << 16) : 0u);
    Frag f0, f1;
    f0.a0 = cpy(hh ? 0u : dg); f0.a1 = cpy(0u); f0.a2 = cpy(0u); f0.a3 = cpy(f0.a0);
    f1.a0 = cpy(hh ? dg : 0u); f1.a1 = cpy(0u); f1.a2 = cpy(0u); f1.a3 = cpy(f1.a0);
    wg_fence();
    far_step<0, 32>(acc2, f0, d2); far_step<1, 32>(acc2, f1, d2);
    wg_commit();
  }
  stsm4(sF + Y_BLK, PK4(acc2, 4));
  SEND(F_OFF + Y_BLK, F_OWN, OFF_RAW + 4 * Y_OWN + wg * Y_BLK, Y_BLK, barY + 8)
  uint32_t rs[13];
  raw_load<13>(rs, gS, 2);
  {
    const unsigned tag = (epoch + 1) & 0xFFFFu;
    int it = 0;
    while (((((uint32_t)gv >> 16) != tag) || (((uint32_t)(gv >> 48)) != tag)) && ++it < (1 << 20))
      asm volatile("ld.relaxed.gpu.global.b64 %0, [%1];" : "=l"(gv) : "l"(P.gate + wg * 512 + rank * 256 + 2 * (tid_now() & 127)) : "memory");
  }
  const uint32_t g2 = __byte_perm((uint32_t)gv, (uint32_t)(gv >> 32), 0x5410);
  auto finalize = [&]() {
    const int tx = tid_now() & 127;
    const uint32_t off = wg * Y_BLK + ((tx >> 2) & 3) * Y_PLANE + (7 - (tx >> 4)) * 16 + (tx & 3) * 4;
    const uint32_t own = sb + OFF_W + Y_OFF + rank * Y_OWN + off, oth = sb + OFF_RAW + off;
    const uint32_t a0 = rank ? oth : own, a1 = rank ? own : oth;
    const uint32_t st0 = rank ? Y_OWN : W_WG, st1 = rank ? W_WG : Y_OWN;
    const uint32_t fown = sb + OFF_W + F_OFF + rank * F_OWN + off, foth = (wg == 1) ? oth + 4 * Y_OWN - Y_BLK : oth + (OFF_FIN - OFF_RAW) - 2 * Y_BLK;
    const uint32_t fst = (wg == 1) ? Y_BLK : 2 * Y_BLK;
    const uint32_t f0 = rank ? foth : fown, f1 = rank ? fown : foth, ft0 = rank ? fst : W_WG, ft1 = rank ? W_WG : fst;
    const uint32_t og = bsub(0x3F803F80u, g2);
    uint4* dst = P.out + (size_t)(wg * 512 + rank * 256 + 2 * tx) * 64 + clus;
    mbar_wait(barY, 0);
    uint32_t ya[8], yb[8];
    #pragma unroll
    for (int c = 0; c < 4; c++) {
      ya[c] = lds32(a0 + c * st0); yb[c] = lds32(a0 + c * st0 + 4 * Y_PLANE);
      ya[4 + c] = lds32(a1 + c * st1); yb[4 + c] = lds32(a1 + c * st1 + 4 * Y_PLANE);
    }
    if (wg) {
      mbar_wait(barY + (wg == 1 ? 8 : 16), 0);
      #pragma unroll
      for (int c = 0; c < 4; c++) {
        ya[c] = badd(ya[c], lds32(f0 + c * ft0)); yb[c] = badd(yb[c], lds32(f0 + c * ft0 + 4 * Y_PLANE));
        ya[4 + c] = badd(ya[4 + c], lds32(f1 + c * ft1)); yb[4 + c] = badd(yb[4 + c], lds32(f1 + c * ft1 + 4 * Y_PLANE));
      }
    }
    TICK(9);
    uint32_t o[8];
    #pragma unroll
    for (int c = 0; c < 8; c++) o[c] = badd(bmul(g2, ya[c]), bmul(og, yb[c]));
    asm volatile("red.global.add.noftz.v4.bf16x2 [%0], {%1,%2,%3,%4};" :: "l"(dst),
      "r"(__byte_perm(o[0], o[1], 0x5410)), "r"(__byte_perm(o[2], o[3], 0x5410)), "r"(__byte_perm(o[4], o[5], 0x5410)), "r"(__byte_perm(o[6], o[7], 0x5410)) : "memory");
    asm volatile("red.global.add.noftz.v4.bf16x2 [%0], {%1,%2,%3,%4};" :: "l"(dst + 64),
      "r"(__byte_perm(o[0], o[1], 0x7632)), "r"(__byte_perm(o[2], o[3], 0x7632)), "r"(__byte_perm(o[4], o[5], 0x7632)), "r"(__byte_perm(o[6], o[7], 0x7632)) : "memory");
  };
  if (wg == 0) finalize();
  wg_wait<0>();
  redef<12>(acc2);
  s3_group<-1, 24>(acc2, rs, m7, d7, d9);
  s3_group<-3, 24>(acc2, rs + 4, m7, d7, d9);
  s3_group<-5, 24>(acc2, rs + 8, m7, d7, d9);
  wg_wait<0>();
  fence_regs<16>(acc2);
  TICK(8);
  stsm4(sF + 3 * Y_BLK, PK4(acc2, 0)); stsm4(sF + 2 * Y_BLK, PK4(acc2, 2));
  SEND(F_OFF + 2 * Y_BLK, F_OWN, OFF_FIN + wg * 2 * Y_BLK, 2 * Y_BLK, barY + 16)
  if (wg) finalize();
  asm volatile("barrier.cluster.arrive.relaxed.aligned;" ::: "memory");
  TICK(10);
#undef PK4
#undef SEND
#undef TAILS
  asm volatile("barrier.cluster.wait.aligned;" ::: "memory");
  if (blockIdx.x == 0 && tid_now() == 0) *P.epoch = epoch + 1;
}

typedef CUresult (*EncodeFn)(CUtensorMap*, CUtensorMapDataType, cuuint32_t, void*, const cuuint64_t*, const cuuint64_t*, const cuuint32_t*,
                             const cuuint32_t*, CUtensorMapInterleave, CUtensorMapSwizzle, CUtensorMapL2promotion, CUtensorMapFloatOOBfill);

}

extern "C" void kernel_launch(void* const* d_in, const int* in_sizes, int n_in, void* d_out, int out_size) {
  static EncodeFn enc = nullptr;
  static unsigned *gate_ptr = nullptr, *epoch_ptr = nullptr;
  if (!enc) {
    cudaGetSymbolAddress((void**)&gate_ptr, g_gate);
    cudaGetSymbolAddress((void**)&epoch_ptr, g_epoch);
    cudaFuncSetAttribute(s4d_kernel, cudaFuncAttributeMaxDynamicSharedMemorySize, SMEM_BYTES);
    void* fn = nullptr; cudaDriverEntryPointQueryResult qr;
    cudaGetDriverEntryPoint("cuTensorMapEncodeTiled", &fn, cudaEnableDefault, &qr);
    enc = (EncodeFn)fn;
  }
  CUtensorMap tm;
  {
    cuuint64_t gd[2] = {512, 2048}; cuuint64_t gs[1] = {1024}; cuuint32_t box[2] = {8, 256}; cuuint32_t es[2] = {1, 1};
    enc(&tm, CU_TENSOR_MAP_DATA_TYPE_BFLOAT16, 2, d_in[0], gd, gs, box, es, CU_TENSOR_MAP_INTERLEAVE_NONE, CU_TENSOR_MAP_SWIZZLE_NONE,
        L2PROMO, CU_TENSOR_MAP_FLOAT_OOB_FILL_NONE);
  }
  Params P;
  P.u = (const uint4*)d_in[0];
  for (int b = 0; b < 2; b++) {
    P.logA[b] = (const uint32_t*)d_in[1 + 7 * b];
    P.Aim[b] = (const uint32_t*)d_in[2 + 7 * b];
    P.Cre[b] = (const uint32_t*)d_in[3 + 7 * b];
    P.Cim[b] = (const uint32_t*)d_in[4 + 7 * b];
    P.logdt[b] = (const uint16_t*)d_in[5 + 7 * b];
    P.Dsk[b] = (const uint16_t*)d_in[6 + 7 * b];
  }
  P.gw = (const uint4*)d_in[14];
  P.out = (uint4*)d_out;
  P.gate = gate_ptr; P.epoch = epoch_ptr;
  s4d_kernel<<<128, 512, SMEM_BYTES>>>(P, tm);
}
```

```cpp
#include <cuda_runtime.h>
#include <cuda.h>
#include <cuda_bf16.h>
#include <cuda_fp16.h>
#include <stdint.h>

#define TMADELAY 0
#define TMADEP
#define L2PROMO CU_TENSOR_MAP_L2_PROMOTION_NONE

#define STAGGER 0
#define VIN 1
#define EARLY0 1
#define ONESEED 1
#define F16ACC 1
#define PRE 0
namespace {

constexpr int U1_PLANE = 1184;
constexpr int U1_CH    = 4 * U1_PLANE + 16;
constexpr int OFF_RAW  = 0;
constexpr int OFF_MISC = 32768;
constexpr int OFF_U1   = OFF_MISC + 384;
constexpr int T_D = 0, T_P3 = 1188, T_P5 = 1448, T_P7 = 1708, T_P9 = 1916, CP = 2112, T_BR = 2 * CP;
constexpr int OFF_T    = OFF_U1 + 4 * U1_CH + 64;
constexpr int R_WARP   = 66 * 128;
constexpr int W_WG     = 4 * R_WARP;
constexpr int OFF_W    = OFF_T + 8 * T_BR;
constexpr int V3_OFF = 0, V5_OFF = 3584, V7_OFF = 7168, V9_OFF = 10240, V2_OFF = 13312;
constexpr int Y_PLANE  = 160, Y_BLK = 8 * Y_PLANE, Y_OWN = 4 * Y_BLK, Y_OFF = 15360, F_OFF = Y_OFF + 2 * Y_OWN - Y_BLK, F_OWN = 3 * Y_BLK;
constexpr int OFF_FIN  = OFF_W + 4 * W_WG;
constexpr int SMEM_BYTES = OFF_FIN + 4 * 2 * Y_BLK;
static_assert(OFF_T % 128 == 0 && OFF_W % 128 == 0 && W_WG % 128 == 0 && F_OFF + Y_BLK + 2 * F_OWN <= W_WG && 4 * Y_OWN + 4 * Y_BLK <= 32768 && SMEM_BYTES <= 232448, "smem");

__device__ unsigned g_epoch;
__device__ unsigned g_gate[2048];

struct Params {
  const uint4* u;
  const uint32_t* logA[2];
  const uint32_t* Aim[2];
  const uint32_t* Cre[2];
  const uint32_t* Cim[2];
  const uint16_t* logdt[2];
  const uint16_t* Dsk[2];
  const uint4* gw;
  uint4* out;
  unsigned* gate;
  unsigned* epoch;
};

template<int N, int TB> __device__ __forceinline__ void wgmma_rs(float* d, uint32_t a0, uint32_t a1, uint32_t a2, uint32_t a3, uint64_t desc);
template<int N, int TB> __device__ __forceinline__ void wgmma_rs_first(float* d, uint32_t a0, uint32_t a1, uint32_t a2, uint32_t a3, uint64_t desc);
template<> __device__ __forceinline__ void wgmma_rs<64,0>(float* d, uint32_t a0, uint32_t a1, uint32_t a2, uint32_t a3, uint64_t desc) {
  asm volatile("wgmma.mma_async.sync.aligned.m64n64k16.f32.bf16.bf16 {%0,%1,%2,%3,%4,%5,%6,%7,%8,%9,%10,%11,%12,%13,%14,%15,%16,%17,%18,%19,%20,%21,%22,%23,%24,%25,%26,%27,%28,%29,%30,%31}, {%32,%33,%34,%35}, %36, 1, 1, 1, 0;"
    : "+f"(d[0]), "+f"(d[1]), "+f"(d[2]), "+f"(d[3]), "+f"(d[4]), "+f"(d[5]), "+f"(d[6]), "+f"(d[7]), "+f"(d[8]), "+f"(d[9]), "+f"(d[10]), "+f"(d[11]), "+f"(d[12]), "+f"(d[13]), "+f"(d[14]), "+f"(d[15]), "+f"(d[16]), "+f"(d[17]), "+f"(d[18]), "+f"(d[19]), "+f"(d[20]), "+f"(d[21]), "+f"(d[22]), "+f"(d[23]), "+f"(d[24]), "+f"(d[25]), "+f"(d[26]), "+f"(d[27]), "+f"(d[28]), "+f"(d[29]), "+f"(d[30]), "+f"(d[31])
    : "r"(a0), "r"(a1), "r"(a2), "r"(a3), "l"(desc));
}
template<> __device__ __forceinline__ void wgmma_rs<56,0>(float* d, uint32_t a0, uint32_t a1, uint32_t a2, uint32_t a3, uint64_t desc) {
  asm volatile("wgmma.mma_async.sync.aligned.m64n56k16.f32.bf16.bf16 {%0,%1,%2,%3,%4,%5,%6,%7,%8,%9,%10,%11,%12,%13,%14,%15,%16,%17,%18,%19,%20,%21,%22,%23,%24,%25,%26,%27}, {%28,%29,%30,%31}, %32, 1, 1, 1, 0;"
    : "+f"(d[0]), "+f"(d[1]), "+f"(d[2]), "+f"(d[3]), "+f"(d[4]), "+f"(d[5]), "+f"(d[6]), "+f"(d[7]), "+f"(d[8]), "+f"(d[9]), "+f"(d[10]), "+f"(d[11]), "+f"(d[12]), "+f"(d[13]), "+f"(d[14]), "+f"(d[15]), "+f"(d[16]), "+f"(d[17]), "+f"(d[18]), "+f"(d[19]), "+f"(d[20]), "+f"(d[21]), "+f"(d[22]), "+f"(d[23]), "+f"(d[24]), "+f"(d[25]), "+f"(d[26]), "+f"(d[27])
    : "r"(a0), "r"(a1), "r"(a2), "r"(a3), "l"(desc));
}
template<> __device__ __forceinline__ void wgmma_rs<48,1>(float* d, uint32_t a0, uint32_t a1, uint32_t a2, uint32_t a3, uint64_t desc) {
  asm volatile("wgmma.mma_async.sync.aligned.m64n48k16.f32.bf16.bf16 {%0,%1,%2,%3,%4,%5,%6,%7,%8,%9,%10,%11,%12,%13,%14,%15,%16,%17,%18,%19,%20,%21,%22,%23}, {%24,%25,%26,%27}, %28, 1, 1, 1, 1;"
    : "+f"(d[0]), "+f"(d[1]), "+f"(d[2]), "+f"(d[3]), "+f"(d[4]), "+f"(d[5]), "+f"(d[6]), "+f"(d[7]), "+f"(d[8]), "+f"(d[9]), "+f"(d[10]), "+f"(d[11]), "+f"(d[12]), "+f"(d[13]), "+f"(d[14]), "+f"(d[15]), "+f"(d[16]), "+f"(d[17]), "+f"(d[18]), "+f"(d[19]), "+f"(d[20]), "+f"(d[21]), "+f"(d[22]), "+f"(d[23])
    : "r"(a0), "r"(a1), "r"(a2), "r"(a3), "l"(desc));
}
template<> __device__ __forceinline__ void wgmma_rs<32,1>(float* d, uint32_t a0, uint32_t a1, uint32_t a2, uint32_t a3, uint64_t desc) {
  asm volatile("wgmma.mma_async.sync.aligned.m64n32k16.f32.bf16.bf16 {%0,%1,%2,%3,%4,%5,%6,%7,%8,%9,%10,%11,%12,%13,%14,%15}, {%16,%17,%18,%19}, %20, 1, 1, 1, 1;"
    : "+f"(d[0]), "+f"(d[1]), "+f"(d[2]), "+f"(d[3]), "+f"(d[4]), "+f"(d[5]), "+f"(d[6]), "+f"(d[7]), "+f"(d[8]), "+f"(d[9]), "+f"(d[10]), "+f"(d[11]), "+f"(d[12]), "+f"(d[13]), "+f"(d[14]), "+f"(d[15])
    : "r"(a0), "r"(a1), "r"(a2), "r"(a3), "l"(desc));
}
template<> __device__ __forceinline__ void wgmma_rs<16,1>(float* d, uint32_t a0, uint32_t a1, uint32_t a2, uint32_t a3, uint64_t desc) {
  asm volatile("wgmma.mma_async.sync.aligned.m64n16k16.f32.bf16.bf16 {%0,%1,%2,%3,%4,%5,%6,%7}, {%8,%9,%10,%11}, %12, 1, 1, 1, 1;"
    : "+f"(d[0]), "+f"(d[1]), "+f"(d[2]), "+f"(d[3]), "+f"(d[4]), "+f"(d[5]), "+f"(d[6]), "+f"(d[7])
    : "r"(a0), "r"(a1), "r"(a2), "r"(a3), "l"(desc));
}
template<> __device__ __forceinline__ void wgmma_rs_first<64,0>(float* d, uint32_t a0, uint32_t a1, uint32_t a2, uint32_t a3, uint64_t desc) {
  asm volatile("wgmma.mma_async.sync.aligned.m64n64k16.f32.bf16.bf16 {%0,%1,%2,%3,%4,%5,%6,%7,%8,%9,%10,%11,%12,%13,%14,%15,%16,%17,%18,%19,%20,%21,%22,%23,%24,%25,%26,%27,%28,%29,%30,%31}, {%32,%33,%34,%35}, %36, 0, 1, 1, 0;"
    : "=f"(d[0]), "=f"(d[1]), "=f"(d[2]), "=f"(d[3]), "=f"(d[4]), "=f"(d[5]), "=f"(d[6]), "=f"(d[7]), "=f"(d[8]), "=f"(d[9]), "=f"(d[10]), "=f"(d[11]), "=f"(d[12]), "=f"(d[13]), "=f"(d[14]), "=f"(d[15]), "=f"(d[16]), "=f"(d[17]), "=f"(d[18]), "=f"(d[19]), "=f"(d[20]), "=f"(d[21]), "=f"(d[22]), "=f"(d[23]), "=f"(d[24]), "=f"(d[25]), "=f"(d[26]), "=f"(d[27]), "=f"(d[28]), "=f"(d[29]), "=f"(d[30]), "=f"(d[31])
    : "r"(a0), "r"(a1), "r"(a2), "r"(a3), "l"(desc));
}
template<> __device__ __forceinline__ void wgmma_rs_first<48,1>(float* d, uint32_t a0, uint32_t a1, uint32_t a2, uint32_t a3, uint64_t desc) {
  asm volatile("wgmma.mma_async.sync.aligned.m64n48k16.f32.bf16.bf16 {%0,%1,%2,%3,%4,%5,%6,%7,%8,%9,%10,%11,%12,%13,%14,%15,%16,%17,%18,%19,%20,%21,%22,%23}, {%24,%25,%26,%27}, %28, 0, 1, 1, 1;"
    : "=f"(d[0]), "=f"(d[1]), "=f"(d[2]), "=f"(d[3]), "=f"(d[4]), "=f"(d[5]), "=f"(d[6]), "=f"(d[7]), "=f"(d[8]), "=f"(d[9]), "=f"(d[10]), "=f"(d[11]), "=f"(d[12]), "=f"(d[13]), "=f"(d[14]), "=f"(d[15]), "=f"(d[16]), "=f"(d[17]), "=f"(d[18]), "=f"(d[19]), "=f"(d[20]), "=f"(d[21]), "=f"(d[22]), "=f"(d[23])
    : "r"(a0), "r"(a1), "r"(a2), "r"(a3), "l"(desc));
}
template<> __device__ __forceinline__ void wgmma_rs_first<32,1>(float* d, uint32_t a0, uint32_t a1, uint32_t a2, uint32_t a3, uint64_t desc) {
  asm volatile("wgmma.mma_async.sync.aligned.m64n32k16.f32.bf16.bf16 {%0,%1,%2,%3,%4,%5,%6,%7,%8,%9,%10,%11,%12,%13,%14,%15}, {%16,%17,%18,%19}, %20, 0, 1, 1, 1;"
    : "=f"(d[0]), "=f"(d[1]), "=f"(d[2]), "=f"(d[3]), "=f"(d[4]), "=f"(d[5]), "=f"(d[6]), "=f"(d[7]), "=f"(d[8]), "=f"(d[9]), "=f"(d[10]), "=f"(d[11]), "=f"(d[12]), "=f"(d[13]), "=f"(d[14]), "=f"(d[15])
    : "r"(a0), "r"(a1), "r"(a2), "r"(a3), "l"(desc));
}
template<> __device__ __forceinline__ void wgmma_rs_first<16,1>(float* d, uint32_t a0, uint32_t a1, uint32_t a2, uint32_t a3, uint64_t desc) {
  asm volatile("wgmma.mma_async.sync.aligned.m64n16k16.f32.bf16.bf16 {%0,%1,%2,%3,%4,%5,%6,%7}, {%8,%9,%10,%11}, %12, 0, 1, 1, 1;"
    : "=f"(d[0]), "=f"(d[1]), "=f"(d[2]), "=f"(d[3]), "=f"(d[4]), "=f"(d[5]), "=f"(d[6]), "=f"(d[7])
    : "r"(a0), "r"(a1), "r"(a2), "r"(a3), "l"(desc));
}

__device__ __forceinline__ void wg_fence()  { asm volatile("wgmma.fence.sync.aligned;" ::: "memory"); }
__device__ __forceinline__ void wg_commit() { asm volatile("wgmma.commit_group.sync.aligned;\n wgmma.wait_group.sync.aligned 1;" ::: "memory"); }
template<int N> __device__ __forceinline__ void wg_wait() { asm volatile("wgmma.wait_group.sync.aligned %0;" :: "n"(N) : "memory"); }
template<int N> __device__ __forceinline__ void fence_regs(float* d) {
  #pragma unroll
  for (int i = 0; i < N; i++) asm volatile("" : "+f"(d[i]) :: "memory");
}
template<int N> __device__ __forceinline__ void redef(float* d) {
  #pragma unroll
  for (int i = 0; i < N; i++) { float y; asm volatile("mov.b32 %0, %1;" : "=f"(y) : "f"(d[i])); d[i] = y; }
}
__device__ __forceinline__ uint64_t mkdesc(uint32_t addr, uint32_t lbo, uint32_t sbo) {
  return (uint64_t)((addr & 0x3FFFF) >> 4) | ((uint64_t)(lbo >> 4) << 16) | ((uint64_t)(sbo >> 4) << 32);
}
__device__ __forceinline__ void bar_sync(int id, int n) { asm volatile("bar.sync %0, %1;" :: "r"(id), "r"(n) : "memory"); }
__device__ __forceinline__ uint32_t lds32(uint32_t a) { uint32_t v; asm volatile("ld.shared.u32 %0, [%1];" : "=r"(v) : "r"(a)); return v; }
__device__ __forceinline__ uint4 lds128(uint32_t a) { uint4 v; asm volatile("ld.shared.v4.u32 {%0,%1,%2,%3}, [%4];" : "=r"(v.x), "=r"(v.y), "=r"(v.z), "=r"(v.w) : "r"(a)); return v; }
__device__ __forceinline__ void bar_arrive(int id, int n) { asm volatile("bar.arrive %0, %1;" :: "r"(id), "r"(n) : "memory"); }
__device__ __forceinline__ void ldsm4t(uint32_t& r0, uint32_t& r1, uint32_t& r2, uint32_t& r3, uint32_t a) {
  asm volatile("ldmatrix.sync.aligned.m8n8.x4.trans.shared.b16 {%0,%1,%2,%3}, [%4];" : "=r"(r0), "=r"(r1), "=r"(r2), "=r"(r3) : "r"(a) : "memory");
}
__device__ __forceinline__ void ldsm4(uint32_t& r0, uint32_t& r1, uint32_t& r2, uint32_t& r3, uint32_t a) {
  asm volatile("ldmatrix.sync.aligned.m8n8.x4.shared.b16 {%0,%1,%2,%3}, [%4];" : "=r"(r0), "=r"(r1), "=r"(r2), "=r"(r3) : "r"(a) : "memory");
}
__device__ __forceinline__ void stsm4(uint32_t a, uint32_t r0, uint32_t r1, uint32_t r2, uint32_t r3) {
  asm volatile("stmatrix.sync.aligned.m8n8.x4.shared.b16 [%0], {%1,%2,%3,%4};" :: "r"(a), "r"(r0), "r"(r1), "r"(r2), "r"(r3) : "memory");
}
__device__ __forceinline__ void stsm4t(uint32_t a, uint32_t r0, uint32_t r1, uint32_t r2, uint32_t r3) {
  asm volatile("stmatrix.sync.aligned.m8n8.x4.trans.shared.b16 [%0], {%1,%2,%3,%4};" :: "r"(a), "r"(r0), "r"(r1), "r"(r2), "r"(r3) : "memory");
}
__device__ __forceinline__ void sts16(uint32_t a, uint32_t v) { asm volatile("st.shared.u16 [%0], %1;" :: "r"(a), "r"(v) : "memory"); }
__device__ __forceinline__ void sts32(uint32_t a, uint32_t v) { asm volatile("st.shared.u32 [%0], %1;" :: "r"(a), "r"(v) : "memory"); }
__device__ __forceinline__ void sts128(uint32_t a, uint32_t x, uint32_t y, uint32_t z, uint32_t w) { asm volatile("st.shared.v4.u32 [%0], {%1,%2,%3,%4};" :: "r"(a), "r"(x), "r"(y), "r"(z), "r"(w) : "memory"); }
__device__ __forceinline__ uint32_t mapa(uint32_t a, uint32_t r) { uint32_t v; asm("mapa.shared::cluster.u32 %0, %1, %2;" : "=r"(v) : "r"(a), "r"(r)); return v; }
__device__ __forceinline__ float ex2(float x) { float y; asm("ex2.approx.ftz.f32 %0, %1;" : "=f"(y) : "f"(x)); return y; }
__device__ __forceinline__ float fsin(float x) { float y; asm("sin.approx.ftz.f32 %0, %1;" : "=f"(y) : "f"(x)); return y; }
__device__ __forceinline__ float fcos(float x) { float y; asm("cos.approx.ftz.f32 %0, %1;" : "=f"(y) : "f"(x)); return y; }
__device__ __forceinline__ float bf_lo(uint32_t w) { return __uint_as_float(w << 16); }
__device__ __forceinline__ float bf_hi(uint32_t w) { return __uint_as_float(w & 0xFFFF0000u); }
__device__ __forceinline__ uint32_t pk_h(float lo, float hi) { uint32_t d; asm("cvt.rn.f16x2.f32 %0, %1, %2;" : "=r"(d) : "f"(hi), "f"(lo)); return d; }
__device__ __forceinline__ uint32_t pk_bf(float lo, float hi) { uint32_t d; asm("cvt.rn.bf16x2.f32 %0, %1, %2;" : "=r"(d) : "f"(hi), "f"(lo)); return d; }
__device__ __forceinline__ uint32_t badd(uint32_t a, uint32_t b) { uint32_t d; asm("add.rn.bf16x2 %0, %1, %2;" : "=r"(d) : "r"(a), "r"(b)); return d; }
__device__ __forceinline__ uint32_t bmul(uint32_t a, uint32_t b) { uint32_t d; asm("mul.rn.bf16x2 %0, %1, %2;" : "=r"(d) : "r"(a), "r"(b)); return d; }
__device__ __forceinline__ uint32_t bsub(uint32_t a, uint32_t b) { uint32_t d; asm("sub.rn.bf16x2 %0, %1, %2;" : "=r"(d) : "r"(a), "r"(b)); return d; }
struct C2 { uint32_t r, i; };
__device__ __forceinline__ uint32_t hmul(uint32_t a, uint32_t b) { uint32_t d; asm("mul.rn.f16x2 %0, %1, %2;" : "=r"(d) : "r"(a), "r"(b)); return d; }
__device__ __forceinline__ uint32_t hfma(uint32_t a, uint32_t b, uint32_t c) { uint32_t d; asm("fma.rn.f16x2 %0, %1, %2, %3;" : "=r"(d) : "r"(a), "r"(b), "r"(c)); return d; }
__device__ __forceinline__ uint32_t hfnma(uint32_t a, uint32_t b, uint32_t c) {
  uint32_t d; asm("{.reg .b32 t; neg.f16x2 t, %1; fma.rn.f16x2 %0, t, %2, %3;}" : "=r"(d) : "r"(a), "r"(b), "r"(c)); return d;
}
__device__ __forceinline__ C2 cmul(C2 x, C2 z)  { C2 o; o.r = hfnma(x.i, z.i, hmul(x.r, z.r)); o.i = hfma(x.i, z.r, hmul(x.r, z.i)); return o; }
__device__ __forceinline__ C2 cmulc(C2 x, C2 z) { C2 o; o.r = hfma(x.i, z.i, hmul(x.r, z.r)); o.i = hfnma(x.r, z.i, hmul(x.i, z.r)); return o; }
__device__ __forceinline__ void csq(float& r, float& i) { float t = i * i; float n = fmaf(r, r, -t); i = __uint_as_float(__float_as_uint(r * i) + 0x00800000u); r = n; }

#define TICK(k)

__device__ __forceinline__ uint32_t cpy(uint32_t x) { uint32_t y; asm volatile("mov.b32 %0, %1;" : "=r"(y) : "r"(x)); return y; }
__device__ __forceinline__ void keep(uint32_t& x) { asm volatile("" : "+r"(x)); }
__device__ __forceinline__ int tid_now() { int t; asm volatile("mov.u32 %0, %%tid.x;" : "=r"(t)); return t; }
struct Frag { uint32_t a0, a1, a2, a3; };
template<int N> __device__ __forceinline__ void raw_load(uint32_t* raw, uint32_t base, int p) {
  #pragma unroll
  for (int i = 0; i < N; i++) raw[i] = lds32(base - 16 * (p - 1 + i));
}
__device__ __forceinline__ Frag mkfrag(const uint32_t* r, bool first) { Frag f; f.a0 = r[1]; f.a1 = r[2]; f.a2 = first ? r[0] : cpy(r[0]); f.a3 = cpy(r[1]); return f; }
template<int S> __device__ __forceinline__ void dense_step(float* acc, const Frag& f, uint64_t d0) {
  constexpr int kk = S & 1, m = (S + 1) >> 1;
  constexpr int N = (m < 8) ? 64 : 56;
  if constexpr (S == -1) wgmma_rs_first<64, 0>(acc, f.a0, f.a1, f.a2, f.a3, d0 + (uint64_t)((2 * kk * U1_PLANE + m * 16) >> 4));
  else wgmma_rs<N, 0>(acc, f.a0, f.a1, f.a2, f.a3, d0 + (uint64_t)((2 * kk * U1_PLANE + m * 16) >> 4));
}
template<int S0, int NS> __device__ __forceinline__ void dense_load(uint32_t* raw, uint32_t base) {
  #pragma unroll
  for (int i = 1; i <= 2 * NS; i++) raw[i] = lds32(base - 16 * (2 * S0 - 1 + i));
}
template<int S0, int NS, int W> __device__ __forceinline__ void dense_group(float* acc, uint32_t* raw, uint64_t d0) {
  Frag f[3];
  #pragma unroll
  for (int i = 0; i < NS; i++) f[i] = mkfrag(raw + 2 * i, i == 0);
  raw[0] = cpy(raw[2 * NS]);
  wg_fence();
  dense_step<S0>(acc, f[0], d0); dense_step<S0 + 1>(acc, f[1], d0);
  if constexpr (NS > 2) dense_step<S0 + 2>(acc, f[2], d0);
  asm volatile("wgmma.commit_group.sync.aligned;" ::: "memory");
  wg_wait<W>();
}
template<int S, int N, bool FIRST = false, int BS = 512> __device__ __forceinline__ void far_step(float* acc, const Frag& f, uint64_t d0) {
  constexpr int fl = (S >= 0) ? (S / 2) : -((1 - S) / 2);
  if constexpr (FIRST) wgmma_rs_first<N, 1>(acc, f.a0, f.a1, f.a2, f.a3, d0 + (uint64_t)(((-fl) * BS + (S & 1) * 256) >> 4));
  else wgmma_rs<N, 1>(acc, f.a0, f.a1, f.a2, f.a3, d0 + (uint64_t)(((-fl) * BS + (S & 1) * 256) >> 4));
}
template<int S, int N, bool FIRST = false, int BS = 512> __device__ __forceinline__ void far_group(float* acc, const uint32_t* raw, uint64_t da, uint64_t db) {
  const Frag f0 = mkfrag(raw, true), f1 = mkfrag(raw + 2, false), f2 = mkfrag(raw + 5, true), f3 = mkfrag(raw + 7, false);
  wg_fence();
  far_step<S, N, FIRST, BS>(acc, f0, da); far_step<S - 1, N, false, BS>(acc, f1, da); far_step<S, N, false, BS>(acc, f2, db); far_step<S - 1, N, false, BS>(acc, f3, db);
  asm volatile("wgmma.commit_group.sync.aligned;" ::: "memory");
}
__device__ __forceinline__ void mma16816bf(float* c, uint32_t a0, uint32_t a1, uint32_t a2, uint32_t a3, uint32_t b0, uint32_t b1) {
  asm volatile("mma.sync.aligned.m16n8k16.row.col.f32.bf16.bf16.f32 {%0,%1,%2,%3}, {%4,%5,%6,%7}, {%8,%9}, {%0,%1,%2,%3};"
    : "+f"(c[0]), "+f"(c[1]), "+f"(c[2]), "+f"(c[3]) : "r"(a0), "r"(a1), "r"(a2), "r"(a3), "r"(b0), "r"(b1));
}
__device__ __forceinline__ void mbar_wait(uint32_t bar, uint32_t parity) {
  uint32_t ok = 0; int it = 0;
  do {
    asm volatile("{.reg .pred p; mbarrier.try_wait.parity.shared::cta.b64 p, [%1], %2, 20000; selp.u32 %0, 1, 0, p;}" : "=r"(ok) : "r"(bar), "r"(parity) : "memory");
  } while (!ok && ++it < (1 << 16));
}
__device__ __forceinline__ void cexp2(float& r, float& i, float e, float x) {
  const float k = __fadd_rn(fmaf(x, 0.15915494309189535f, 12582912.f), -12582912.f);
  const float m = ex2(e), a = fmaf(k, -6.283185307179586f, x);
  r = m * fcos(a); i = m * fsin(a);
}
__device__ __forceinline__ void mma16816(float* c, uint32_t a0, uint32_t a1, uint32_t a2, uint32_t a3, uint32_t b0, uint32_t b1) {
  asm("mma.sync.aligned.m16n8k16.row.col.f32.f16.f16.f32 {%0,%1,%2,%3}, {%4,%5,%6,%7}, {%8,%9}, {%0,%1,%2,%3};"
    : "+f"(c[0]), "+f"(c[1]), "+f"(c[2]), "+f"(c[3]) : "r"(a0), "r"(a1), "r"(a2), "r"(a3), "r"(b0), "r"(b1));
}
__device__ __forceinline__ void mma16816h(uint32_t* c, uint32_t a0, uint32_t a1, uint32_t a2, uint32_t a3, uint32_t b0, uint32_t b1) {
  asm("mma.sync.aligned.m16n8k16.row.col.f16.f16.f16.f16 {%0,%1}, {%2,%3,%4,%5}, {%6,%7}, {%0,%1};"
    : "+r"(c[0]), "+r"(c[1]) : "r"(a0), "r"(a1), "r"(a2), "r"(a3), "r"(b0), "r"(b1));
}
__device__ __forceinline__ float h_lo(uint32_t w) { return __half2float(__ushort_as_half((unsigned short)(w & 0xFFFFu))); }
__device__ __forceinline__ float h_hi(uint32_t w) { return __half2float(__ushort_as_half((unsigned short)(w >> 16))); }

__device__ __forceinline__ void load_E(uint32_t* E, uint32_t a0, uint32_t a1, uint32_t a2) {
  const uint4 e0 = lds128(a0), e1 = lds128(a1), e2 = lds128(a2);
  E[0] = e0.x; E[1] = e0.y; E[2] = e0.z; E[3] = e0.w; E[4] = e1.x; E[5] = e1.y; E[6] = e1.z; E[7] = e1.w; E[8] = e2.x; E[9] = e2.y; E[10] = e2.z; E[11] = e2.w;
}
template<bool FULL> __device__ __forceinline__ void build_V(const uint32_t* E, uint32_t o8, uint32_t o16, uint32_t o9) {
  uint32_t O[11], Q[11], R[10], V3[11], V5[10];
  #pragma unroll
  for (int n = FULL ? 3 : 4; n <= 10; n++) { O[n] = __byte_perm(E[n - 1], E[n], 0x5432); Q[n] = badd(O[n], E[n - 1]); }
  #pragma unroll
  for (int n = FULL ? 4 : 5; n <= (FULL ? 9 : 8); n++) R[n] = badd(Q[n], Q[n - 1]);
  #pragma unroll
  for (int n = FULL ? 4 : 7; n <= 10; n++) V3[n] = badd(Q[n], O[n - 1]);
  #pragma unroll
  for (int n = 5; n <= (FULL ? 9 : 8); n++) V5[n] = badd(E[n], R[n]);
  sts128(o8 + V3_OFF, V3[7], V3[8], V3[9], V3[10]);
  sts128(o8 + V5_OFF, V5[5], V5[6], V5[7], V5[8]);
  if (FULL) {
    sts128(o16 + V7_OFF, badd(R[6], V3[4]), badd(R[7], V3[5]), badd(R[8], V3[6]), badd(R[9], V3[7]));
    sts128(o9, badd(V5[6], R[4]), badd(V5[7], R[5]), badd(V5[8], R[6]), badd(V5[9], R[7]));
    sts128(o16 + V2_OFF, Q[7], Q[8], Q[9], Q[10]);
  }
}

__global__ void __cluster_dims__(2, 1, 1) __launch_bounds__(512, 1)
s4d_kernel(const __grid_constant__ Params P, const __grid_constant__ CUtensorMap tmU) {
  extern __shared__ __align__(256) uint8_t smem[];
  const int tid = threadIdx.x, lane = tid & 31, wi = __shfl_sync(0xFFFFFFFFu, tid >> 5, 0), wg = wi >> 2, wq = wi & 3;
  const int br = wq >> 1, hh = wq & 1;
  const unsigned pch = blockIdx.x * 4 + wg, pw = pch * 64 + hh * 32;
  const uint32_t wLA = __ldg(P.logA[br] + pw + lane), wAI = __ldg(P.Aim[br] + pw + lane);
  const uint32_t wDT = __ldg(P.logdt[br] + pch);
  const uint32_t wCR = __ldg(P.Cre[br] + pw + lane), wCI = __ldg(P.Cim[br] + pw + lane);
  const uint32_t wCR2 = __ldg(P.Cre[br] + (pw ^ 32) + lane), wCI2 = __ldg(P.Cim[br] + (pw ^ 32) + lane);
  const uint32_t wDS = __ldg(P.Dsk[br] + pch);
  unsigned epoch;
  asm volatile("ld.relaxed.gpu.global.u32 %0, [%1];" : "=r"(epoch) : "l"(P.epoch) : "memory");
  const uint32_t sb = (uint32_t)__cvta_generic_to_shared(smem);
  const int g = lane >> 2, q = lane & 3;
  const int rank = blockIdx.x & 1, clus = blockIdx.x >> 1;
  const uint32_t barU = sb + OFF_MISC, barY = sb + OFF_MISC + 8, junk = sb + OFF_MISC + 128;
  const bool late = wg == 3;

  const uint32_t sT = sb + OFF_T + (wg * 2 + br) * T_BR;
  const uint32_t sU = sb + OFF_U1 + wg * U1_CH;
  const uint32_t sW = sb + OFF_W + wg * W_WG;
  const uint32_t sR = sW + wq * R_WARP;
  const uint32_t l4 = lane * 4, l16 = lane * 16;
  const uint32_t we = sR + l4, wo = sR + (l4 ^ 64);
  #pragma unroll
  for (int k = 0; k < 4; k++) sts128(sT + hh * CP + l16 + k * 512, 0, 0, 0, 0);
  if (lane < 10) {
    sts128(sU + wq * U1_PLANE + 1024 + l16, 0, 0, 0, 0);
    if (lane < 4) sts128(sT + hh * CP + 2048 + l16, 0, 0, 0, 0);
  }
  sts32(we + 48 * 128, 0x3C003C00u); sts32(we + 56 * 128, 0u);
  const bool lo = q < 2, fix = (hh == 0) && !(lane & 29);
  const uint32_t jk = sR + 2560, q64 = (lane & 1) * 64;
  const uint32_t c0 = sT + T_D + 606 - 256 * hh - l4 - 4 * q, p3 = sT + T_P3 + 190 - 32 * hh - 2 * g - q64;
  uint32_t tb0 = sT + T_D + 1116 - 256 * hh - l4;
  uint32_t tcl = lo ? c0 : jk + 2 + l4, tph = lo ? jk + l4 : p3;
  uint32_t tpa = lo ? sT + ((lane & 4) ? T_P7 + 126 : T_P9 + 128) - 16 * hh - (g & 6) - q64 : jk + l4;
  uint32_t tu2 = lo ? c0 - 4 : p3, tu4 = tu2 - (lo ? 128 : 16);
  uint32_t tu3 = tu4 + (lo ? 6 : (T_P5 - T_P3) + 2), tu1 = fix ? jk : tu2 + (lo ? 6 : (T_P5 - T_P3) + 2);
  uint32_t tcf = fix ? jk + 2 : tcl, tphf = fix ? jk : tph, tpaf = fix ? jk : tpa;
  const int rw = (lane & 7) - 4 * rank;
  uint32_t xdst = sb + OFF_U1 + (63 - 8 * ((wi - 4) & 7)) * 16 + (lane >> 3) * U1_PLANE + rw * U1_CH;
  if ((unsigned)rw >= 4u) xdst = junk + 128 + (xdst & 127u);
  const uint32_t xsrc = sb + OFF_RAW + ((wi - 4) & 7) * 4096 + l16;
  uint32_t gL = sT - 32 * hh + ((lane & 4) ? 0 : CP + 2) - 2 * g + 4 * q;
  const int role = (wq + wg) & 3;
  uint32_t ve2 = sU + (63 - 8 * role) * 16 + q * U1_PLANE - g * 16;
  uint32_t ve1 = ve2 + (q == 0 ? 3 * U1_PLANE + 16 : -U1_PLANE), ve0 = ve2 + (lo ? 2 * U1_PLANE + 16 : -2 * U1_PLANE);
  const uint32_t vo8 = sW + (5 - role) * 512 + l16;
  uint32_t vo16 = sW + (1 - (role >> 1)) * 1024 + (role & 1) * 256 + q64 * 8 + (lane >> 1) * 16;
  uint32_t vo9 = vo16 + V9_OFF + ((lane & 1) ? 16 - 512 : 512);
  if (lane == 31 && (role & 1)) vo9 = (role == 3) ? junk : sW + V9_OFF;
  keep(ve0); keep(ve1); keep(ve2); keep(vo16); keep(vo9);
  keep(tb0); keep(tcl); keep(tph); keep(tpa); keep(tu1); keep(tu2); keep(tu3); keep(tu4); keep(tcf); keep(tphf); keep(tpaf); keep(xdst); keep(gL);

  asm volatile("fence.proxy.async.shared::cta;" ::: "memory");
  __syncwarp();
  if (lane == 0 && late) {
    asm volatile("cp.async.bulk.global.shared::cta.bulk_group [%0], [%1], 2048;" :: "l"(P.out + (size_t)(blockIdx.x * 16 + wq * 4) * 64), "r"(sT + hh * CP) : "memory");
    asm volatile("cp.async.bulk.global.shared::cta.bulk_group [%0], [%1], 2048;" :: "l"(P.out + (size_t)(blockIdx.x * 16 + wq * 4 + 2) * 64), "r"(sT + hh * CP) : "memory");
    asm volatile("cp.async.bulk.commit_group;" ::: "memory");
  }
  if (tid == 480) {
    asm volatile("prefetch.tensormap [%0];" :: "l"(&tmU) : "memory");
    asm volatile("mbarrier.init.shared::cta.b64 [%0], 1;" :: "r"(barU) : "memory");
    asm volatile("mbarrier.init.shared::cta.b64 [%0], 8;" :: "r"(barU + 40) : "memory");
    asm volatile("mbarrier.init.shared::cta.b64 [%0], 17;" :: "r"(barY + 24) : "memory");
    asm volatile("mbarrier.init.shared::cta.b64 [%0], 5;" :: "r"(barY) : "memory");
    asm volatile("mbarrier.init.shared::cta.b64 [%0], 17;" :: "r"(barY + 8) : "memory");
    asm volatile("mbarrier.init.shared::cta.b64 [%0], 17;" :: "r"(barY + 16) : "memory");
    asm volatile("mbarrier.arrive.expect_tx.shared::cta.b64 _, [%0], %1;" :: "r"(barU), "r"(32768) : "memory");
    asm volatile("mbarrier.arrive.expect_tx.shared::cta.b64 _, [%0], %1;" :: "r"(barY), "r"(4 * Y_OWN) : "memory");
    asm volatile("mbarrier.arrive.expect_tx.shared::cta.b64 _, [%0], %1;" :: "r"(barY + 8), "r"(4096) : "memory");
    asm volatile("mbarrier.arrive.expect_tx.shared::cta.b64 _, [%0], %1;" :: "r"(barY + 16), "r"(4096) : "memory");
    asm volatile("mbarrier.arrive.expect_tx.shared::cta.b64 _, [%0], %1;" :: "r"(barY + 24), "r"(4096) : "memory");
    asm volatile("fence.mbarrier_init.release.cluster;" ::: "memory");
  }
  __syncwarp();
  asm volatile("barrier.cluster.arrive.relaxed.aligned;" ::: "memory");
  if (wi == 15) {
    asm volatile("barrier.cluster.wait.aligned;" ::: "memory");
    if (lane == 0) {
      #pragma unroll
      for (int k = 0; k < 4; k++)
        asm volatile("cp.async.bulk.tensor.2d.shared::cluster.global.mbarrier::complete_tx::bytes.multicast::cluster [%0], [%1, {%3, %4}], [%2], %5;"
          :: "r"(sb + OFF_RAW + (rank * 1024 + k * 256) * 16 TMADEP), "l"(&tmU), "r"(barU), "r"(clus * 8), "r"(rank * 1024 + k * 256), "h"((unsigned short)3) : "memory");
    }
    __syncwarp();
  }

  const float dt = bf_lo(pk_bf(ex2(bf_lo(wDT) * 1.4426950408889634f), 0.f));
  float csc, tsc;
  {
    uint32_t m = __vmaxu2(__vmaxu2(wCR & 0x7FFF7FFFu, wCI & 0x7FFF7FFFu), __vmaxu2(wCR2 & 0x7FFF7FFFu, wCI2 & 0x7FFF7FFFu));
    m = max(m & 0xFFFFu, m >> 16);
    m = __reduce_max_sync(0xFFFFFFFFu, m);
    int k = 134 - (int)(m >> 7);
    k = min(max(k, -126), 126);
    csc = __uint_as_float((uint32_t)(k + 127) << 23);
    tsc = 2.0f * dt * __uint_as_float((uint32_t)(127 - k) << 23);
  }
  TICK(0);
  {
    const uint32_t Ab = pk_bf(ex2(bf_lo(wLA) * 1.4426950408889634f), ex2(bf_hi(wLA) * 1.4426950408889634f));
    const float ndt = dt * -1.4426950408889634f;
    const float ea = bf_lo(Ab) * ndt, eb = bf_hi(Ab) * ndt, ta = bf_lo(wAI) * dt, tb = bf_hi(wAI) * dt;
    float ra, ia, rb, ib, sa, ja, sb2, jb;
    cexp2(ra, ia, ea, ta); cexp2(rb, ib, eb, tb);
#define PK1 C2{pk_h(ra, rb), pk_h(ia, ib)}
#define PK6 C2{pk_h(sa, sb2), pk_h(ja, jb)}
#define SQ1 csq(ra, ia); csq(rb, ib);
#define SQ6 csq(sa, ja); csq(sb2, jb);
#define PUT(T, G, V) { sts32(((G) & 1 ? wo : we) + ((T) * 16 + (G)) * 128, (V).r); sts32(((G) & 1 ? wo : we) + ((T) * 16 + 8 + (G)) * 128, (V).i); }
    C2 H0[8], X[8], H1[8], H2[5];
    H0[0] = C2{pk_h(bf_lo(wCR) * csc, bf_hi(wCR) * csc), pk_h(bf_lo(wCI) * -csc, bf_hi(wCI) * -csc)}; PUT(0, 0, H0[0])
    const C2 m1 = PK1; H0[1] = cmulc(H0[0], m1); PUT(0, 1, H0[1])
    SQ1 const C2 m2 = PK1;
    H0[2] = cmulc(H0[0], m2); PUT(0, 2, H0[2]) H0[3] = cmulc(H0[1], m2); PUT(0, 3, H0[3])
    SQ1 const C2 m4 = PK1;
    H0[4] = cmulc(H0[0], m4); PUT(0, 4, H0[4]) H0[5] = cmulc(H0[1], m4); PUT(0, 5, H0[5])
    SQ1 X[1] = PK1; PUT(3, 1, X[1])
    H0[6] = cmulc(H0[2], m4); PUT(0, 6, H0[6]) H0[7] = cmulc(H0[3], m4); PUT(0, 7, H0[7])
    SQ1 X[2] = PK1; PUT(3, 2, X[2])
    X[3] = cmul(X[2], X[1]); PUT(3, 3, X[3])
    SQ1 X[4] = PK1; PUT(3, 4, X[4])
    X[5] = cmul(X[4], X[1]); PUT(3, 5, X[5]) X[6] = cmul(X[4], X[2]); PUT(3, 6, X[6])
    SQ1 const C2 Z = PK1;
    sts32(we + 64 * 128, Z.r); sts32(we + 65 * 128, Z.i);
    X[7] = cmul(X[6], X[1]); PUT(3, 7, X[7])
    SQ1 SQ1 const C2 m256 = PK1;
    H1[0] = cmulc(H0[0], m256); PUT(1, 0, H1[0]) H1[1] = cmulc(H0[2], m256); PUT(1, 1, H1[1])
    SQ1 const C2 m512 = PK1;
    H1[2] = cmulc(H0[4], m256); PUT(1, 2, H1[2]) H1[3] = cmulc(H0[6], m256); PUT(1, 3, H1[3])
    SQ1 const C2 m1k = PK1;
    H1[4] = cmulc(H0[0], m512); PUT(1, 4, H1[4]) H1[5] = cmulc(H0[4], m512); PUT(1, 5, H1[5])
    H1[6] = cmulc(H1[0], m512); PUT(1, 6, H1[6]) H1[7] = cmulc(H1[2], m512); PUT(1, 7, H1[7])
    H2[0] = cmulc(H0[0], m1k); PUT(2, 0, H2[0]) H2[1] = cmulc(H1[0], m1k); PUT(2, 1, H2[1])
    H2[2] = cmulc(H1[4], m1k); PUT(2, 2, H2[2]) H2[3] = cmulc(H1[6], m1k); PUT(2, 3, H2[3])
    H2[4] = cmulc(H2[0], m1k); PUT(2, 4, H2[4])
#undef PUT
#undef PK1
#undef PK6
#undef SQ1
#undef SQ6
  }
  if (wi != 15) asm volatile("barrier.cluster.wait.aligned;" ::: "memory");
  __syncwarp();
  TICK(1);
  uint32_t cD[2][3][2];
  #pragma unroll
  for (int i = 0; i < 12; i++) (&cD[0][0][0])[i] = 0u;
#define mma16816 mma16816h
  {
    #pragma unroll
    for (int h2 = 0; h2 < 2; h2++) {
      const uint32_t r0 = sR + g * 128 + 16 * ((q + 4 * h2) ^ (4 * (g & 1))), zb = sR + 64 * 128 + 16 * (q + 4 * h2);
      const uint4 Xr = lds128(r0 + 48 * 128), Xi = lds128(r0 + 56 * 128), Zr = lds128(zb), Zi = lds128(zb + 128);
      const uint4 H0r = lds128(r0), H0i = lds128(r0 + 8 * 128), H1r = lds128(r0 + 16 * 128), H1i = lds128(r0 + 24 * 128);
      const uint4 H2r = lds128(r0 + 32 * 128), H2i = lds128(r0 + 40 * 128);
#define KSTEP(E, F) { \
      const C2 za = C2{Zr.E, Zi.E}, zc = C2{Zr.F, Zi.F}, a0 = C2{Xr.E, Xi.E}, c0 = C2{Xr.F, Xi.F}; \
      const C2 a1 = cmul(a0, za), c1 = cmul(c0, zc), a2 = cmul(a1, za), c2 = cmul(c1, zc), a3 = cmul(a2, za), c3 = cmul(c2, zc); \
      mma16816(cD[0][0], a0.r, a1.r, c0.r, c1.r, H0r.E, H0r.F); mma16816(cD[0][1], a0.r, a1.r, c0.r, c1.r, H1r.E, H1r.F); \
      mma16816(cD[0][2], a0.r, a1.r, c0.r, c1.r, H2r.E, H2r.F); \
      mma16816(cD[0][0], a0.i, a1.i, c0.i, c1.i, H0i.E, H0i.F); mma16816(cD[0][1], a0.i, a1.i, c0.i, c1.i, H1i.E, H1i.F); \
      mma16816(cD[0][2], a0.i, a1.i, c0.i, c1.i, H2i.E, H2i.F); \
      mma16816(cD[1][0], a2.r, a3.r, c2.r, c3.r, H0r.E, H0r.F); mma16816(cD[1][1], a2.r, a3.r, c2.r, c3.r, H1r.E, H1r.F); \
      mma16816(cD[1][2], a2.r, a3.r, c2.r, c3.r, H2r.E, H2r.F); \
      mma16816(cD[1][0], a2.i, a3.i, c2.i, c3.i, H0i.E, H0i.F); mma16816(cD[1][1], a2.i, a3.i, c2.i, c3.i, H1i.E, H1i.F); \
      mma16816(cD[1][2], a2.i, a3.i, c2.i, c3.i, H2i.E, H2i.F); }
      KSTEP(x, y) KSTEP(z, w)
#undef KSTEP
    }
  }
  __syncwarp();
  TICK(2);
  uint4 gx[8], gw0, gw1;
  if (late) {
    const size_t grow = (size_t)(blockIdx.x * 16 + wq * 4) * 64 + lane;
    #pragma unroll
    for (int r = 0; r < 8; r++) gx[r] = __ldg(P.u + grow + r * 32);
    gw0 = __ldg(P.gw + lane); gw1 = __ldg(P.gw + 32 + lane);
  } else if (wg) {
    mbar_wait(barU, 0);
    TICK(4);
    #pragma unroll
    for (int k = 0; k < 8; k += 4) {
      uint32_t r[4][4];
      #pragma unroll
      for (int j = 0; j < 4; j++) ldsm4t(r[j][0], r[j][1], r[j][2], r[j][3], xsrc + (k + j) * 512);
      #pragma unroll
      for (int j = 0; j < 4; j++) stsm4(xdst - 16 * (k + j), r[j][0], r[j][1], r[j][2], r[j][3]);
    }
    asm volatile("fence.proxy.async.shared::cta;" ::: "memory");
    __syncwarp();
    if (lane == 0) asm volatile("mbarrier.arrive.shared::cta.b64 _, [%0];" :: "r"(barU + 40) : "memory");
  }
  asm volatile("barrier.cluster.arrive.relaxed.aligned;" ::: "memory");
  float v[12];
  {
    const uint32_t sO = sW + (wq ^ 1) * R_WARP + lane * 16, sS = sR + lane * 16;
#define XCH(SND, KEEP) \
    sts128(sS, cD[SND][0][0], cD[SND][0][1], cD[SND][1][0], cD[SND][1][1]); sts128(sS + 512, cD[SND][2][0], cD[SND][2][1], 0u, 0u); \
    bar_sync(1 + wg * 2 + br, 64); \
    { const uint4 o = lds128(sO), p = lds128(sO + 512); const uint32_t w[6] = {o.x, o.y, o.z, o.w, p.x, p.y}; \
      _Pragma("unroll") for (int k = 0; k < 6; k++) { \
        v[2 * k] = (h_lo(cD[KEEP][k >> 1][k & 1]) + h_lo(w[k])) * tsc; v[2 * k + 1] = (h_hi(cD[KEEP][k >> 1][k & 1]) + h_hi(w[k])) * tsc; } }
    if (hh) { XCH(0, 1) } else { XCH(1, 0) }
#undef XCH
  }
  uint32_t w1f = 0, w2f = 0;
  {
    if (hh == 0 && lane == 0) v[0] += bf_lo(wDS);
    #pragma unroll
    for (int a = 0; a < 2; a++) {
      const uint32_t w0 = pk_bf(v[2 * a + 1], v[2 * a]);
      sts32(tb0 - 128 * a, w0);
      sts16(tb0 - 128 * a + CP + 4, w0 >> 16);
      sts16(tb0 - 128 * a + CP + 2, w0);
      const uint32_t w1 = pk_bf(v[4 + 2 * a], v[5 + 2 * a]);
      const uint32_t aa = __byte_perm(w1, 0, 0x1010), ba = __byte_perm(w1, 0, 0x1032);
      sts16(a ? tu3 : tu1, w1);
      sts16(a ? tu4 : tu2, ba);
      const uint32_t w2 = pk_bf(v[8 + 2 * a], v[9 + 2 * a]);
      sts32(tcl - 128 * a - 2, aa);
      sts32((a ? tcl : tcf) - 128 * a + CP + 2, aa);
      sts32(tcl - 128 * a + CP - 2, ba);
      sts16((a ? tph : tphf) - 16 * a + T_P5 - T_P3 + CP + 4, w1);
      sts16(tph - 16 * a + CP + 2, ba);
      sts16((a ? tpa : tpaf) - 8 * a, w2); sts16((a ? tpa : tpaf) - 8 * a + CP + 2, w2);
      sts16(tpa - 8 * a - 32, w2 >> 16); sts16(tpa - 8 * a - 32 + CP + 2, w2 >> 16);
      if (a == 0) { w1f = aa; w2f = w2; }
    }
    if (fix) {
      if (q == 0) {
        sts16(sT + T_D + CP + 2 * (560 - 256), w1f);
        sts16(sT + T_P5 + 64, w2f); sts16(sT + T_P5 + CP + 66, w2f);
      } else {
        sts32(sT + T_D + 92, w1f); sts16(sT + T_D + 96, w1f); sts16(sT + T_D + 90, w1f);
        sts32(sT + T_D + CP + 96, w1f); sts32(sT + T_D + CP + 92, w1f);
        sts16(sT + T_P9, w2f); sts16(sT + T_P9 + CP + 2, w2f);
      }
    }
  }
  TICK(3);

  if (late) {
    float s01[4] = {0.f, 0.f, 0.f, 0.f}, s23[4] = {0.f, 0.f, 0.f, 0.f};
    const uint32_t one = 0x3F803F80u;
#define GMMA(S, A, B, W) mma16816bf(S, bmul(A.x, W.x), bmul(B.x, W.x), bmul(A.y, W.y), bmul(B.y, W.y), one, one); \
                         mma16816bf(S, bmul(A.z, W.z), bmul(B.z, W.z), bmul(A.w, W.w), bmul(B.w, W.w), one, one);
    GMMA(s01, gx[0], gx[2], gw0) GMMA(s23, gx[4], gx[6], gw0) GMMA(s01, gx[1], gx[3], gw1) GMMA(s23, gx[5], gx[7], gw1)
#undef GMMA
    float s = (q & 2) ? ((q & 1) ? s23[2] : s23[0]) : ((q & 1) ? s01[2] : s01[0]);
    s += __shfl_xor_sync(0xFFFFFFFFu, s, 4); s += __shfl_xor_sync(0xFFFFFFFFu, s, 8); s += __shfl_xor_sync(0xFFFFFFFFu, s, 16);
    s = bf_lo(pk_bf(s, 0.f));
    const float gv = __fdividef(1.0f, 1.0f + ex2(s * -1.4426950408889634f));
    const uint32_t gpub = ((epoch + 1) << 16) | (pk_bf(gv, 0.f) & 0xFFFFu);
    if (lane == 0) asm volatile("cp.async.bulk.wait_group 0;" ::: "memory");
    __syncwarp();
    if (lane < 4) asm volatile("st.relaxed.gpu.global.u32 [%0], %1;" :: "l"(P.gate + blockIdx.x * 16 + wq * 4 + lane), "r"(gpub) : "memory");
    TICK(5);
  }
  mbar_wait(barU + 40, 0);
  bar_sync(9 + wg, 128);
  TICK(6);
  const uint32_t g3 = gL + T_P3 + 190, g5 = gL + T_P5 + 190, g7 = gL + T_P7 + 126, g9 = gL + T_P9 + 126, gD = gL + T_D + 1118;
  const uint32_t sV = sW;
#define PK4(A, B) pk_bf(A[4 * (B)], A[4 * (B) + 1]), pk_bf(A[4 * (B) + 2], A[4 * (B) + 3]), pk_bf(A[4 * (B) + 4], A[4 * (B) + 5]), pk_bf(A[4 * (B) + 6], A[4 * (B) + 7])
#define PUSHV(V, DST, BAR) \
    asm volatile("st.async.shared::cluster.mbarrier::complete_tx::bytes.v4.b32 [%0], {%1,%2,%3,%4}, [%5];" \
      :: "r"(mapa(DST, rank ^ 1)), "r"(V.x), "r"(V.y), "r"(V.z), "r"(V.w), "r"(mapa(BAR, rank ^ 1)) : "memory");
#define ARRIVE(BAR) if ((tid_now() & 31) == 0) asm volatile("mbarrier.arrive.shared::cta.b64 _, [%0];" :: "r"(BAR) : "memory");

  float acc1[32], accA[24], accB[16], accS[16], accT[8];
  uint32_t raw[10];
  const uint64_t dU = mkdesc(sU, U1_PLANE, 128);
  raw_load<7>(raw, gD, -2);
  {
    uint32_t E[12], E2[12];
    load_E(E, ve0, ve1, ve2);
    if (role < 2) load_E(E2, ve0 - 512, ve1 - 512, ve2 - 512);
    dense_group<-1, 3, 2>(acc1, raw, dU);
    dense_load<2, 3>(raw, gD);
    build_V<true>(E, vo8, vo16, vo9);
    if (role < 2) build_V<false>(E2, vo8 - 2048, 0, 0);
    else {
      sts128(sV + l16 + (role & 1) * V5_OFF + 3072, 0, 0, 0, 0);
      if (role == 3 && lane == 0) sts128(sV + V9_OFF + 1024, 0, 0, 0, 0);
    }
  }
  TICK(11);
  dense_group<2, 3, 2>(acc1, raw, dU);
  dense_load<5, 3>(raw, gD);
  dense_group<5, 3, 2>(acc1, raw, dU);
  dense_load<8, 3>(raw, gD);
  asm volatile("fence.proxy.async.shared::cta;" ::: "memory");
  dense_group<8, 3, 2>(acc1, raw, dU);
  dense_load<11, 2>(raw, gD);
  dense_group<11, 2, 2>(acc1, raw, dU);
  dense_load<13, 2>(raw, gD);
  dense_group<13, 2, 2>(acc1, raw, dU);
  dense_load<15, 3>(raw, gD);
  wg_wait<0>();
  redef<28>(acc1);
  TICK(12);
  dense_group<15, 3, 2>(acc1, raw, dU);
  dense_load<18, 3>(raw, gD);
  dense_group<18, 3, 2>(acc1, raw, dU);
  dense_load<21, 3>(raw, gD);
  bar_sync(9 + wg, 128);
  dense_group<21, 3, 2>(acc1, raw, dU);
  dense_load<24, 3>(raw, gD);
  dense_group<24, 3, 2>(acc1, raw, dU);
  dense_load<27, 3>(raw, gD);
  unsigned long long gv;
  asm volatile("ld.relaxed.gpu.global.b64 %0, [%1];" : "=l"(gv) : "l"(P.gate + wg * 512 + rank * 256 + 2 * (tid_now() & 127)) : "memory");
  dense_group<27, 3, 2>(acc1, raw, dU);
  dense_load<30, 2>(raw, gD);
  dense_group<30, 2, 2>(acc1, raw, dU);
  dense_load<32, 2>(raw, gD);
  dense_group<32, 2, 1>(acc1, raw, dU);

  TICK(13);
  const uint64_t d3 = mkdesc(sV + V3_OFF, 128, 512), d5 = mkdesc(sV + V5_OFF, 128, 512);
  const uint64_t d7 = mkdesc(sV + V7_OFF, 128, 512), d9 = mkdesc(sV + V9_OFF, 128, 512), d2 = mkdesc(sV + V2_OFF, 128, 512);
  uint32_t rb[10];
  raw_load<5>(raw, g3, -2); raw_load<5>(raw + 5, g5, -2);
  raw_load<4>(rb + 1, g3, 3); raw_load<4>(rb + 6, g5, 3);
  rb[0] = cpy(raw[4]); rb[5] = cpy(raw[9]);
  far_group<1, 48, true>(accA, raw, d3, d5);
  far_group<-1, 48>(accA, rb, d3, d5);
  wg_wait<2>();
  fence_regs<32>(acc1);
  TICK(7);
  uint32_t sF, uF, sS3;
  {
    const int ln = tid_now(), mat = (ln >> 3) & 3, r8 = ln & 7;
    const uint32_t uo = (br * 4 + 2 * hh + (mat & 1)) * Y_PLANE + r8 * 16;
    const uint32_t sY = sW + Y_OFF + (1 - (mat >> 1)) * Y_OWN + uo;
    stsm4t(sY + 3 * Y_BLK, PK4(acc1, 0)); stsm4t(sY + 2 * Y_BLK, PK4(acc1, 2));
    stsm4t(sY + Y_BLK, PK4(acc1, 4)); stsm4t(sY, PK4(acc1, 6));
    raw_load<5>(raw, g3, 6); raw_load<5>(raw + 5, g5, 6);
    far_group<-3, 32, true>(accB, raw, d3, d5);
    asm volatile("barrier.cluster.wait.aligned;" ::: "memory");
    asm volatile("fence.proxy.async.shared::cta;" ::: "memory");
    bar_sync(9 + wg, 128);
    if ((ln & 127) == 0) {
      asm volatile("cp.async.bulk.shared::cluster.shared::cta.mbarrier::complete_tx::bytes [%0], [%1], %2, [%3];"
        :: "r"(mapa(sb + OFF_RAW + wg * Y_OWN, rank ^ 1)), "r"(sW + Y_OFF + (rank ^ 1) * Y_OWN), "r"(Y_OWN), "r"(mapa(barY, rank ^ 1)) : "memory");
      asm volatile("mbarrier.arrive.shared::cta.b64 _, [%0];" :: "r"(barY) : "memory");
    }
    uF = (br * 4 + (r8 & 3)) * Y_PLANE + (7 - 4 * hh - 2 * (mat & 1) - (r8 >> 2)) * 16;
    sF = sW + F_OFF + (1 - (mat >> 1)) * F_OWN + uF;
    sS3 = (br * 4 + 2 * (r8 & 1) + (mat >> 1)) * Y_PLANE + (7 - 4 * (mat & 1) - (r8 >> 1)) * 16;
  }
  wg_wait<1>();
  fence_regs<24>(accA);
  TICK(14);
  raw_load<5>(raw, g7, -2); raw_load<5>(raw + 5, g9, -2);
  rb[0] = cpy(raw[4]); rb[5] = cpy(raw[9]);
  const uint32_t f1k = lds32(sT + T_P5 + 64);
  stsm4(sF + Y_BLK, PK4(accA, 4));
  {
    const int ln = tid_now() & 31, df = (ln >> 2) - 2 * (ln & 3);
    const uint32_t b = f1k & 0xFFFFu, dg = (df == 0) ? b : ((df == 1) ? (b << 16) : 0u);
    const Frag f0 = mkfrag(raw, true), f1 = mkfrag(raw + 2, false), f2 = mkfrag(raw + 5, true), f3 = mkfrag(raw + 7, false);
    Frag f4, f5;
    f4.a0 = cpy(hh ? 0u : dg); f4.a1 = cpy(0u); f4.a2 = cpy(0u); f4.a3 = cpy(f4.a0);
    f5.a0 = cpy(hh ? dg : 0u); f5.a1 = cpy(0u); f5.a2 = cpy(0u); f5.a3 = cpy(f5.a0);
    wg_fence();
    far_step<1, 32, true, 1024>(accS, f0, d7); far_step<0, 32, false, 1024>(accS, f1, d7);
    far_step<1, 32, false, 1024>(accS, f2, d9); far_step<0, 32, false, 1024>(accS, f3, d9);
    far_step<0, 32>(accS, f4, d2); far_step<1, 32>(accS, f5, d2);
    asm volatile("wgmma.commit_group.sync.aligned;" ::: "memory");
  }
  __syncwarp();
  {
    const uint4 v = lds128(sW + F_OFF + (rank ^ 1) * F_OWN + Y_BLK + uF);
    if ((tid_now() & 16) == 0) PUSHV(v, sb + OFF_RAW + 4 * Y_OWN + wg * Y_BLK + uF, barY + 8)
    ARRIVE(barY + 8)
  }
  {
    const unsigned tag = (epoch + 1) & 0xFFFFu;
    int it = 0;
    while (((((uint32_t)gv >> 16) != tag) || (((uint32_t)(gv >> 48)) != tag)) && ++it < (1 << 20))
      asm volatile("ld.relaxed.gpu.global.b64 %0, [%1];" : "=l"(gv) : "l"(P.gate + wg * 512 + rank * 256 + 2 * (tid_now() & 127)) : "memory");
  }
  const uint32_t g2 = __byte_perm((uint32_t)gv, (uint32_t)(gv >> 32), 0x5410);
  auto finalize = [&]() {
    uint32_t ya[8], yb[8], f0, f1, ft0, ft1;
    uint4* dst;
    const int tx = tid_now() & 127;
    const uint32_t off = wg * Y_BLK + ((tx >> 2) & 3) * Y_PLANE + (7 - (tx >> 4)) * 16 + (tx & 3) * 4;
    const uint32_t own = sb + OFF_W + Y_OFF + rank * Y_OWN + off, oth = sb + OFF_RAW + off;
    const uint32_t a0 = rank ? oth : own, a1 = rank ? own : oth;
    const uint32_t st0 = rank ? Y_OWN : W_WG, st1 = rank ? W_WG : Y_OWN;
    const uint32_t fown = sb + OFF_W + F_OFF + rank * F_OWN + off, foth = (wg == 1) ? oth + 4 * Y_OWN - Y_BLK : oth + (OFF_FIN - OFF_RAW) - 2 * Y_BLK;
    const uint32_t fst = (wg == 1) ? Y_BLK : 2 * Y_BLK;
    f0 = rank ? foth : fown; f1 = rank ? fown : foth; ft0 = rank ? fst : W_WG; ft1 = rank ? W_WG : fst;
    dst = P.out + (size_t)(wg * 512 + rank * 256 + 2 * tx) * 64 + clus;
    mbar_wait(barY, 0);
    #pragma unroll
    for (int c = 0; c < 4; c++) {
      ya[c] = lds32(a0 + c * st0); yb[c] = lds32(a0 + c * st0 + 4 * Y_PLANE);
      ya[4 + c] = lds32(a1 + c * st1); yb[4 + c] = lds32(a1 + c * st1 + 4 * Y_PLANE);
    }
    if (wg) {
      mbar_wait(barY + 8 * wg, 0);
      #pragma unroll
      for (int c = 0; c < 4; c++) {
        ya[c] = badd(ya[c], lds32(f0 + c * ft0)); yb[c] = badd(yb[c], lds32(f0 + c * ft0 + 4 * Y_PLANE));
        ya[4 + c] = badd(ya[4 + c], lds32(f1 + c * ft1)); yb[4 + c] = badd(yb[4 + c], lds32(f1 + c * ft1 + 4 * Y_PLANE));
      }
    }
    TICK(9);
    const uint32_t og = bsub(0x3F803F80u, g2);
    uint32_t o[8];
    #pragma unroll
    for (int c = 0; c < 8; c++) o[c] = badd(bmul(g2, ya[c]), bmul(og, yb[c]));
    asm volatile("red.global.add.noftz.v4.bf16x2 [%0], {%1,%2,%3,%4};" :: "l"(dst),
      "r"(__byte_perm(o[0], o[1], 0x5410)), "r"(__byte_perm(o[2], o[3], 0x5410)), "r"(__byte_perm(o[4], o[5], 0x5410)), "r"(__byte_perm(o[6], o[7], 0x5410)) : "memory");
    asm volatile("red.global.add.noftz.v4.bf16x2 [%0], {%1,%2,%3,%4};" :: "l"(dst + 64),
      "r"(__byte_perm(o[0], o[1], 0x7632)), "r"(__byte_perm(o[2], o[3], 0x7632)), "r"(__byte_perm(o[4], o[5], 0x7632)), "r"(__byte_perm(o[6], o[7], 0x7632)) : "memory");
  };
  if (wg < PRE) finalize();
  wg_wait<1>();
  raw_load<4>(rb + 1, g7, 3); raw_load<4>(rb + 6, g9, 3);
  far_group<-1, 16, true, 1024>(accT, rb, d7, d9);
  fence_regs<16>(accB);
  #pragma unroll
  for (int i = 0; i < 16; i++) accA[i] += accB[i];
  stsm4(sF + 3 * Y_BLK, PK4(accA, 0)); stsm4(sF + 2 * Y_BLK, PK4(accA, 2));
  TICK(15);
  bar_sync(1 + wg * 2 + br, 64);
  uint32_t fp[8];
  const uint32_t aS3 = sW + F_OFF + hh * F_OWN + sS3;
  ldsm4(fp[0], fp[1], fp[2], fp[3], aS3 + 3 * Y_BLK); ldsm4(fp[4], fp[5], fp[6], fp[7], aS3 + 2 * Y_BLK);
  wg_wait<1>();
  fence_regs<16>(accS);
  #pragma unroll
  for (int i = 4; i < 8; i++) { accS[2 * i] += bf_lo(fp[i]); accS[2 * i + 1] += bf_hi(fp[i]); }
  stsm4(aS3 + 2 * Y_BLK, PK4(accS, 2));
  __syncwarp();
  if (hh != rank) { const uint4 v = lds128(aS3 + 2 * Y_BLK); PUSHV(v, sb + OFF_FIN + wg * 2 * Y_BLK + sS3, barY + 16) }
  ARRIVE(barY + 16)
  #pragma unroll
  for (int i = 0; i < 4; i++) { accS[2 * i] += bf_lo(fp[i]); accS[2 * i + 1] += bf_hi(fp[i]); }
  wg_wait<0>();
  fence_regs<8>(accT);
  TICK(8);
  #pragma unroll
  for (int i = 0; i < 8; i++) accS[i] += accT[i];
  stsm4(aS3 + 3 * Y_BLK, PK4(accS, 0));
  __syncwarp();
  if (hh != rank) { const uint4 v = lds128(aS3 + 3 * Y_BLK); PUSHV(v, sb + OFF_FIN + wg * 2 * Y_BLK + Y_BLK + sS3, barY + 24) }
  ARRIVE(barY + 24)
  if (wg >= PRE) finalize();
  asm volatile("barrier.cluster.arrive.relaxed.aligned;" ::: "memory");
  TICK(10);
#undef PK4
#undef PUSHV
#undef ARRIVE
  asm volatile("barrier.cluster.wait.aligned;" ::: "memory");
  if (blockIdx.x == 0 && tid_now() == 0) *P.epoch = epoch + 1;
}

typedef CUresult (*EncodeFn)(CUtensorMap*, CUtensorMapDataType, cuuint32_t, void*, const cuuint64_t*, const cuuint64_t*, const cuuint32_t*,
                             const cuuint32_t*, CUtensorMapInterleave, CUtensorMapSwizzle, CUtensorMapL2promotion, CUtensorMapFloatOOBfill);

}

extern "C" void kernel_launch(void* const* d_in, const int* in_sizes, int n_in, void* d_out, int out_size) {
  static EncodeFn enc = nullptr;
  static unsigned *gate_ptr = nullptr, *epoch_ptr = nullptr;
  if (!enc) {
    cudaGetSymbolAddress((void**)&gate_ptr, g_gate);
    cudaGetSymbolAddress((void**)&epoch_ptr, g_epoch);
    cudaFuncSetAttribute(s4d_kernel, cudaFuncAttributeMaxDynamicSharedMemorySize, SMEM_BYTES);
    void* fn = nullptr; cudaDriverEntryPointQueryResult qr;
    cudaGetDriverEntryPoint("cuTensorMapEncodeTiled", &fn, cudaEnableDefault, &qr);
    enc = (EncodeFn)fn;
  }
  CUtensorMap tm;
  {
    cuuint64_t gd[2] = {512, 2048}; cuuint64_t gs[1] = {1024}; cuuint32_t box[2] = {8, 256}; cuuint32_t es[2] = {1, 1};
    enc(&tm, CU_TENSOR_MAP_DATA_TYPE_BFLOAT16, 2, d_in[0], gd, gs, box, es, CU_TENSOR_MAP_INTERLEAVE_NONE, CU_TENSOR_MAP_SWIZZLE_NONE,
        L2PROMO, CU_TENSOR_MAP_FLOAT_OOB_FILL_NONE);
  }
  Params P;
  P.u = (const uint4*)d_in[0];
  for (int b = 0; b < 2; b++) {
    P.logA[b] = (const uint32_t*)d_in[1 + 7 * b];
    P.Aim[b] = (const uint32_t*)d_in[2 + 7 * b];
    P.Cre[b] = (const uint32_t*)d_in[3 + 7 * b];
    P.Cim[b] = (const uint32_t*)d_in[4 + 7 * b];
    P.logdt[b] = (const uint16_t*)d_in[5 + 7 * b];
    P.Dsk[b] = (const uint16_t*)d_in[6 + 7 * b];
  }
  P.gw = (const uint4*)d_in[14];
  P.out = (uint4*)d_out;
  P.gate = gate_ptr; P.epoch = epoch_ptr;
  s4d_kernel<<<128, 512, SMEM_BYTES>>>(P, tm);
}
```

```cpp
#include <cuda_runtime.h>
#include <cuda.h>
#include <cuda_bf16.h>
#include <cuda_fp16.h>
#include <stdint.h>

namespace {

constexpr int U1_PLANE = 1184;
constexpr int U1_CH    = 4 * U1_PLANE + 16;
constexpr int OFF_RAW  = 0;
constexpr int OFF_MISC = 32768;
constexpr int OFF_U1   = OFF_MISC + 384;
constexpr int T_D = 0, T_P3 = 1188, T_P5 = 1448, T_P7 = 1708, T_P9 = 1916, CP = 2112, T_BR = 2 * CP;
constexpr int OFF_T    = OFF_U1 + 4 * U1_CH + 64;
constexpr int R_WARP   = 66 * 128;
constexpr int W_WG     = 4 * R_WARP;
constexpr int OFF_W    = OFF_T + 8 * T_BR;
constexpr int V3_OFF = 0, V5_OFF = 3584, V7_OFF = 7168, V9_OFF = 10240, V2_OFF = 13312;
constexpr int Y_PLANE  = 160, Y_BLK = 8 * Y_PLANE, Y_OWN = 4 * Y_BLK, Y_OFF = 15360, F_OFF = Y_OFF + 2 * Y_OWN - Y_BLK, F_OWN = 3 * Y_BLK;
constexpr int OFF_FIN  = OFF_W + 4 * W_WG;
constexpr int SMEM_BYTES = OFF_FIN + 4 * 2 * Y_BLK;
static_assert(OFF_T % 128 == 0 && OFF_W % 128 == 0 && W_WG % 128 == 0 && F_OFF + Y_BLK + 2 * F_OWN <= W_WG && 4 * Y_OWN + 4 * Y_BLK <= 32768 && SMEM_BYTES <= 232448, "smem");

__device__ unsigned g_epoch;
__device__ unsigned g_gate[2048];

struct Params {
  const uint4* u;
  const uint32_t* logA[2];
  const uint32_t* Aim[2];
  const uint32_t* Cre[2];
  const uint32_t* Cim[2];
  const uint16_t* logdt[2];
  const uint16_t* Dsk[2];
  const uint4* gw;
  uint4* out;
  unsigned* gate;
  unsigned* epoch;
};

template<int N, int TB> __device__ __forceinline__ void wgmma_rs(float* d, uint32_t a0, uint32_t a1, uint32_t a2, uint32_t a3, uint64_t desc);
template<int N, int TB> __device__ __forceinline__ void wgmma_rs_first(float* d, uint32_t a0, uint32_t a1, uint32_t a2, uint32_t a3, uint64_t desc);
template<> __device__ __forceinline__ void wgmma_rs<64,0>(float* d, uint32_t a0, uint32_t a1, uint32_t a2, uint32_t a3, uint64_t desc) {
  asm volatile("wgmma.mma_async.sync.aligned.m64n64k16.f32.bf16.bf16 {%0,%1,%2,%3,%4,%5,%6,%7,%8,%9,%10,%11,%12,%13,%14,%15,%16,%17,%18,%19,%20,%21,%22,%23,%24,%25,%26,%27,%28,%29,%30,%31}, {%32,%33,%34,%35}, %36, 1, 1, 1, 0;"
    : "+f"(d[0]), "+f"(d[1]), "+f"(d[2]), "+f"(d[3]), "+f"(d[4]), "+f"(d[5]), "+f"(d[6]), "+f"(d[7]), "+f"(d[8]), "+f"(d[9]), "+f"(d[10]), "+f"(d[11]), "+f"(d[12]), "+f"(d[13]), "+f"(d[14]), "+f"(d[15]), "+f"(d[16]), "+f"(d[17]), "+f"(d[18]), "+f"(d[19]), "+f"(d[20]), "+f"(d[21]), "+f"(d[22]), "+f"(d[23]), "+f"(d[24]), "+f"(d[25]), "+f"(d[26]), "+f"(d[27]), "+f"(d[28]), "+f"(d[29]), "+f"(d[30]), "+f"(d[31])
    : "r"(a0), "r"(a1), "r"(a2), "r"(a3), "l"(desc));
}
template<> __device__ __forceinline__ void wgmma_rs<56,0>(float* d, uint32_t a0, uint32_t a1, uint32_t a2, uint32_t a3, uint64_t desc) {
  asm volatile("wgmma.mma_async.sync.aligned.m64n56k16.f32.bf16.bf16 {%0,%1,%2,%3,%4,%5,%6,%7,%8,%9,%10,%11,%12,%13,%14,%15,%16,%17,%18,%19,%20,%21,%22,%23,%24,%25,%26,%27}, {%28,%29,%30,%31}, %32, 1, 1, 1, 0;"
    : "+f"(d[0]), "+f"(d[1]), "+f"(d[2]), "+f"(d[3]), "+f"(d[4]), "+f"(d[5]), "+f"(d[6]), "+f"(d[7]), "+f"(d[8]), "+f"(d[9]), "+f"(d[10]), "+f"(d[11]), "+f"(d[12]), "+f"(d[13]), "+f"(d[14]), "+f"(d[15]), "+f"(d[16]), "+f"(d[17]), "+f"(d[18]), "+f"(d[19]), "+f"(d[20]), "+f"(d[21]), "+f"(d[22]), "+f"(d[23]), "+f"(d[24]), "+f"(d[25]), "+f"(d[26]), "+f"(d[27])
    : "r"(a0), "r"(a1), "r"(a2), "r"(a3), "l"(desc));
}
template<> __device__ __forceinline__ void wgmma_rs<48,1>(float* d, uint32_t a0, uint32_t a1, uint32_t a2, uint32_t a3, uint64_t desc) {
  asm volatile("wgmma.mma_async.sync.aligned.m64n48k16.f32.bf16.bf16 {%0,%1,%2,%3,%4,%5,%6,%7,%8,%9,%10,%11,%12,%13,%14,%15,%16,%17,%18,%19,%20,%21,%22,%23}, {%24,%25,%26,%27}, %28, 1, 1, 1, 1;"
    : "+f"(d[0]), "+f"(d[1]), "+f"(d[2]), "+f"(d[3]), "+f"(d[4]), "+f"(d[5]), "+f"(d[6]), "+f"(d[7]), "+f"(d[8]), "+f"(d[9]), "+f"(d[10]), "+f"(d[11]), "+f"(d[12]), "+f"(d[13]), "+f"(d[14]), "+f"(d[15]), "+f"(d[16]), "+f"(d[17]), "+f"(d[18]), "+f"(d[19]), "+f"(d[20]), "+f"(d[21]), "+f"(d[22]), "+f"(d[23])
    : "r"(a0), "r"(a1), "r"(a2), "r"(a3), "l"(desc));
}
template<> __device__ __forceinline__ void wgmma_rs<32,1>(float* d, uint32_t a0, uint32_t a1, uint32_t a2, uint32_t a3, uint64_t desc) {
  asm volatile("wgmma.mma_async.sync.aligned.m64n32k16.f32.bf16.bf16 {%0,%1,%2,%3,%4,%5,%6,%7,%8,%9,%10,%11,%12,%13,%14,%15}, {%16,%17,%18,%19}, %20, 1, 1, 1, 1;"
    : "+f"(d[0]), "+f"(d[1]), "+f"(d[2]), "+f"(d[3]), "+f"(d[4]), "+f"(d[5]), "+f"(d[6]), "+f"(d[7]), "+f"(d[8]), "+f"(d[9]), "+f"(d[10]), "+f"(d[11]), "+f"(d[12]), "+f"(d[13]), "+f"(d[14]), "+f"(d[15])
    : "r"(a0), "r"(a1), "r"(a2), "r"(a3), "l"(desc));
}
template<> __device__ __forceinline__ void wgmma_rs<16,1>(float* d, uint32_t a0, uint32_t a1, uint32_t a2, uint32_t a3, uint64_t desc) {
  asm volatile("wgmma.mma_async.sync.aligned.m64n16k16.f32.bf16.bf16 {%0,%1,%2,%3,%4,%5,%6,%7}, {%8,%9,%10,%11}, %12, 1, 1, 1, 1;"
    : "+f"(d[0]), "+f"(d[1]), "+f"(d[2]), "+f"(d[3]), "+f"(d[4]), "+f"(d[5]), "+f"(d[6]), "+f"(d[7])
    : "r"(a0), "r"(a1), "r"(a2), "r"(a3), "l"(desc));
}
template<> __device__ __forceinline__ void wgmma_rs_first<64,0>(float* d, uint32_t a0, uint32_t a1, uint32_t a2, uint32_t a3, uint64_t desc) {
  asm volatile("wgmma.mma_async.sync.aligned.m64n64k16.f32.bf16.bf16 {%0,%1,%2,%3,%4,%5,%6,%7,%8,%9,%10,%11,%12,%13,%14,%15,%16,%17,%18,%19,%20,%21,%22,%23,%24,%25,%26,%27,%28,%29,%30,%31}, {%32,%33,%34,%35}, %36, 0, 1, 1, 0;"
    : "=f"(d[0]), "=f"(d[1]), "=f"(d[2]), "=f"(d[3]), "=f"(d[4]), "=f"(d[5]), "=f"(d[6]), "=f"(d[7]), "=f"(d[8]), "=f"(d[9]), "=f"(d[10]), "=f"(d[11]), "=f"(d[12]), "=f"(d[13]), "=f"(d[14]), "=f"(d[15]), "=f"(d[16]), "=f"(d[17]), "=f"(d[18]), "=f"(d[19]), "=f"(d[20]), "=f"(d[21]), "=f"(d[22]), "=f"(d[23]), "=f"(d[24]), "=f"(d[25]), "=f"(d[26]), "=f"(d[27]), "=f"(d[28]), "=f"(d[29]), "=f"(d[30]), "=f"(d[31])
    : "r"(a0), "r"(a1), "r"(a2), "r"(a3), "l"(desc));
}
template<> __device__ __forceinline__ void wgmma_rs_first<48,1>(float* d, uint32_t a0, uint32_t a1, uint32_t a2, uint32_t a3, uint64_t desc) {
  asm volatile("wgmma.mma_async.sync.aligned.m64n48k16.f32.bf16.bf16 {%0,%1,%2,%3,%4,%5,%6,%7,%8,%9,%10,%11,%12,%13,%14,%15,%16,%17,%18,%19,%20,%21,%22,%23}, {%24,%25,%26,%27}, %28, 0, 1, 1, 1;"
    : "=f"(d[0]), "=f"(d[1]), "=f"(d[2]), "=f"(d[3]), "=f"(d[4]), "=f"(d[5]), "=f"(d[6]), "=f"(d[7]), "=f"(d[8]), "=f"(d[9]), "=f"(d[10]), "=f"(d[11]), "=f"(d[12]), "=f"(d[13]), "=f"(d[14]), "=f"(d[15]), "=f"(d[16]), "=f"(d[17]), "=f"(d[18]), "=f"(d[19]), "=f"(d[20]), "=f"(d[21]), "=f"(d[22]), "=f"(d[23])
    : "r"(a0), "r"(a1), "r"(a2), "r"(a3), "l"(desc));
}
template<> __device__ __forceinline__ void wgmma_rs_first<32,1>(float* d, uint32_t a0, uint32_t a1, uint32_t a2, uint32_t a3, uint64_t desc) {
  asm volatile("wgmma.mma_async.sync.aligned.m64n32k16.f32.bf16.bf16 {%0,%1,%2,%3,%4,%5,%6,%7,%8,%9,%10,%11,%12,%13,%14,%15}, {%16,%17,%18,%19}, %20, 0, 1, 1, 1;"
    : "=f"(d[0]), "=f"(d[1]), "=f"(d[2]), "=f"(d[3]), "=f"(d[4]), "=f"(d[5]), "=f"(d[6]), "=f"(d[7]), "=f"(d[8]), "=f"(d[9]), "=f"(d[10]), "=f"(d[11]), "=f"(d[12]), "=f"(d[13]), "=f"(d[14]), "=f"(d[15])
    : "r"(a0), "r"(a1), "r"(a2), "r"(a3), "l"(desc));
}
template<> __device__ __forceinline__ void wgmma_rs_first<16,1>(float* d, uint32_t a0, uint32_t a1, uint32_t a2, uint32_t a3, uint64_t desc) {
  asm volatile("wgmma.mma_async.sync.aligned.m64n16k16.f32.bf16.bf16 {%0,%1,%2,%3,%4,%5,%6,%7}, {%8,%9,%10,%11}, %12, 0, 1, 1, 1;"
    : "=f"(d[0]), "=f"(d[1]), "=f"(d[2]), "=f"(d[3]), "=f"(d[4]), "=f"(d[5]), "=f"(d[6]), "=f"(d[7])
    : "r"(a0), "r"(a1), "r"(a2), "r"(a3), "l"(desc));
}

__device__ __forceinline__ void wg_fence()  { asm volatile("wgmma.fence.sync.aligned;" ::: "memory"); }
template<int N> __device__ __forceinline__ void wg_wait() { asm volatile("wgmma.wait_group.sync.aligned %0;" :: "n"(N) : "memory"); }
template<int N> __device__ __forceinline__ void fence_regs(float* d) {
  #pragma unroll
  for (int i = 0; i < N; i++) asm volatile("" : "+f"(d[i]) :: "memory");
}
template<int N> __device__ __forceinline__ void redef(float* d) {
  #pragma unroll
  for (int i = 0; i < N; i++) { float y; asm volatile("mov.b32 %0, %1;" : "=f"(y) : "f"(d[i])); d[i] = y; }
}
__device__ __forceinline__ uint64_t mkdesc(uint32_t addr, uint32_t lbo, uint32_t sbo) {
  return (uint64_t)((addr & 0x3FFFF) >> 4) | ((uint64_t)(lbo >> 4) << 16) | ((uint64_t)(sbo >> 4) << 32);
}
__device__ __forceinline__ void bar_sync(int id, int n) { asm volatile("bar.sync %0, %1;" :: "r"(id), "r"(n) : "memory"); }
__device__ __forceinline__ uint32_t lds32(uint32_t a) { uint32_t v; asm volatile("ld.shared.u32 %0, [%1];" : "=r"(v) : "r"(a)); return v; }
__device__ __forceinline__ uint4 lds128(uint32_t a) { uint4 v; asm volatile("ld.shared.v4.u32 {%0,%1,%2,%3}, [%4];" : "=r"(v.x), "=r"(v.y), "=r"(v.z), "=r"(v.w) : "r"(a)); return v; }
__device__ __forceinline__ void ldsm4t(uint32_t& r0, uint32_t& r1, uint32_t& r2, uint32_t& r3, uint32_t a) {
  asm volatile("ldmatrix.sync.aligned.m8n8.x4.trans.shared.b16 {%0,%1,%2,%3}, [%4];" : "=r"(r0), "=r"(r1), "=r"(r2), "=r"(r3) : "r"(a) : "memory");
}
__device__ __forceinline__ void ldsm4(uint32_t& r0, uint32_t& r1, uint32_t& r2, uint32_t& r3, uint32_t a) {
  asm volatile("ldmatrix.sync.aligned.m8n8.x4.shared.b16 {%0,%1,%2,%3}, [%4];" : "=r"(r0), "=r"(r1), "=r"(r2), "=r"(r3) : "r"(a) : "memory");
}
__device__ __forceinline__ void stsm4(uint32_t a, uint32_t r0, uint32_t r1, uint32_t r2, uint32_t r3) {
  asm volatile("stmatrix.sync.aligned.m8n8.x4.shared.b16 [%0], {%1,%2,%3,%4};" :: "r"(a), "r"(r0), "r"(r1), "r"(r2), "r"(r3) : "memory");
}
__device__ __forceinline__ void stsm4t(uint32_t a, uint32_t r0, uint32_t r1, uint32_t r2, uint32_t r3) {
  asm volatile("stmatrix.sync.aligned.m8n8.x4.trans.shared.b16 [%0], {%1,%2,%3,%4};" :: "r"(a), "r"(r0), "r"(r1), "r"(r2), "r"(r3) : "memory");
}
__device__ __forceinline__ void sts16(uint32_t a, uint32_t v) { asm volatile("st.shared.u16 [%0], %1;" :: "r"(a), "r"(v) : "memory"); }
__device__ __forceinline__ void sts32(uint32_t a, uint32_t v) { asm volatile("st.shared.u32 [%0], %1;" :: "r"(a), "r"(v) : "memory"); }
__device__ __forceinline__ void sts128(uint32_t a, uint32_t x, uint32_t y, uint32_t z, uint32_t w) { asm volatile("st.shared.v4.u32 [%0], {%1,%2,%3,%4};" :: "r"(a), "r"(x), "r"(y), "r"(z), "r"(w) : "memory"); }
__device__ __forceinline__ uint32_t mapa(uint32_t a, uint32_t r) { uint32_t v; asm("mapa.shared::cluster.u32 %0, %1, %2;" : "=r"(v) : "r"(a), "r"(r)); return v; }
__device__ __forceinline__ float ex2(float x) { float y; asm("ex2.approx.ftz.f32 %0, %1;" : "=f"(y) : "f"(x)); return y; }
__device__ __forceinline__ float fsin(float x) { float y; asm("sin.approx.ftz.f32 %0, %1;" : "=f"(y) : "f"(x)); return y; }
__device__ __forceinline__ float fcos(float x) { float y; asm("cos.approx.ftz.f32 %0, %1;" : "=f"(y) : "f"(x)); return y; }
__device__ __forceinline__ float bf_lo(uint32_t w) { return __uint_as_float(w << 16); }
__device__ __forceinline__ float bf_hi(uint32_t w) { return __uint_as_float(w & 0xFFFF0000u); }
__device__ __forceinline__ uint32_t pk_h(float lo, float hi) { uint32_t d; asm("cvt.rn.f16x2.f32 %0, %1, %2;" : "=r"(d) : "f"(hi), "f"(lo)); return d; }
__device__ __forceinline__ uint32_t pk_bf(float lo, float hi) { uint32_t d; asm("cvt.rn.bf16x2.f32 %0, %1, %2;" : "=r"(d) : "f"(hi), "f"(lo)); return d; }
__device__ __forceinline__ uint32_t badd(uint32_t a, uint32_t b) { uint32_t d; asm("add.rn.bf16x2 %0, %1, %2;" : "=r"(d) : "r"(a), "r"(b)); return d; }
__device__ __forceinline__ uint32_t bmul(uint32_t a, uint32_t b) { uint32_t d; asm("mul.rn.bf16x2 %0, %1, %2;" : "=r"(d) : "r"(a), "r"(b)); return d; }
__device__ __forceinline__ uint32_t bsub(uint32_t a, uint32_t b) { uint32_t d; asm("sub.rn.bf16x2 %0, %1, %2;" : "=r"(d) : "r"(a), "r"(b)); return d; }
struct C2 { uint32_t r, i; };
__device__ __forceinline__ uint32_t hmul(uint32_t a, uint32_t b) { uint32_t d; asm("mul.rn.f16x2 %0, %1, %2;" : "=r"(d) : "r"(a), "r"(b)); return d; }
__device__ __forceinline__ uint32_t hfma(uint32_t a, uint32_t b, uint32_t c) { uint32_t d; asm("fma.rn.f16x2 %0, %1, %2, %3;" : "=r"(d) : "r"(a), "r"(b), "r"(c)); return d; }
__device__ __forceinline__ uint32_t hfnma(uint32_t a, uint32_t b, uint32_t c) {
  uint32_t d; asm("{.reg .b32 t; neg.f16x2 t, %1; fma.rn.f16x2 %0, t, %2, %3;}" : "=r"(d) : "r"(a), "r"(b), "r"(c)); return d;
}
__device__ __forceinline__ C2 cmul(C2 x, C2 z)  { C2 o; o.r = hfnma(x.i, z.i, hmul(x.r, z.r)); o.i = hfma(x.i, z.r, hmul(x.r, z.i)); return o; }
__device__ __forceinline__ C2 cmulc(C2 x, C2 z) { C2 o; o.r = hfma(x.i, z.i, hmul(x.r, z.r)); o.i = hfnma(x.r, z.i, hmul(x.i, z.r)); return o; }
__device__ __forceinline__ void csq(float& r, float& i) { float t = i * i; float n = fmaf(r, r, -t); i = __uint_as_float(__float_as_uint(r * i) + 0x00800000u); r = n; }

__device__ __forceinline__ uint32_t cpy(uint32_t x) { uint32_t y; asm volatile("mov.b32 %0, %1;" : "=r"(y) : "r"(x)); return y; }
__device__ __forceinline__ void keep(uint32_t& x) { asm volatile("" : "+r"(x)); }
__device__ __forceinline__ int tid_now() { int t; asm volatile("mov.u32 %0, %%tid.x;" : "=r"(t)); return t; }
struct Frag { uint32_t a0, a1, a2, a3; };
template<int N> __device__ __forceinline__ void raw_load(uint32_t* raw, uint32_t base, int p) {
  #pragma unroll
  for (int i = 0; i < N; i++) raw[i] = lds32(base - 16 * (p - 1 + i));
}
__device__ __forceinline__ Frag mkfrag(const uint32_t* r, bool first) { Frag f; f.a0 = r[1]; f.a1 = r[2]; f.a2 = first ? r[0] : cpy(r[0]); f.a3 = cpy(r[1]); return f; }
template<int S> __device__ __forceinline__ void dense_step(float* acc, const Frag& f, uint64_t d0) {
  constexpr int kk = S & 1, m = (S + 1) >> 1;
  constexpr int N = (m < 8) ? 64 : 56;
  if constexpr (S == -1) wgmma_rs_first<64, 0>(acc, f.a0, f.a1, f.a2, f.a3, d0 + (uint64_t)((2 * kk * U1_PLANE + m * 16) >> 4));
  else wgmma_rs<N, 0>(acc, f.a0, f.a1, f.a2, f.a3, d0 + (uint64_t)((2 * kk * U1_PLANE + m * 16) >> 4));
}
template<int S0, int NS> __device__ __forceinline__ void dense_load(uint32_t* raw, uint32_t base) {
  #pragma unroll
  for (int i = 1; i <= 2 * NS; i++) raw[i] = lds32(base - 16 * (2 * S0 - 1 + i));
}
template<int S0, int NS, int W> __device__ __forceinline__ void dense_group(float* acc, uint32_t* raw, uint64_t d0) {
  Frag f[3];
  #pragma unroll
  for (int i = 0; i < NS; i++) f[i] = mkfrag(raw + 2 * i, i == 0);
  raw[0] = cpy(raw[2 * NS]);
  wg_fence();
  dense_step<S0>(acc, f[0], d0); dense_step<S0 + 1>(acc, f[1], d0);
  if constexpr (NS > 2) dense_step<S0 + 2>(acc, f[2], d0);
  asm volatile("wgmma.commit_group.sync.aligned;" ::: "memory");
  wg_wait<W>();
}
template<int S, int N, bool FIRST = false, int BS = 512> __device__ __forceinline__ void far_step(float* acc, const Frag& f, uint64_t d0) {
  constexpr int fl = (S >= 0) ? (S / 2) : -((1 - S) / 2);
  if constexpr (FIRST) wgmma_rs_first<N, 1>(acc, f.a0, f.a1, f.a2, f.a3, d0 + (uint64_t)(((-fl) * BS + (S & 1) * 256) >> 4));
  else wgmma_rs<N, 1>(acc, f.a0, f.a1, f.a2, f.a3, d0 + (uint64_t)(((-fl) * BS + (S & 1) * 256) >> 4));
}
template<int S, int N, bool FIRST = false, int BS = 512> __device__ __forceinline__ void far_group(float* acc, const uint32_t* raw, uint64_t da, uint64_t db) {
  const Frag f0 = mkfrag(raw, true), f1 = mkfrag(raw + 2, false), f2 = mkfrag(raw + 5, true), f3 = mkfrag(raw + 7, false);
  wg_fence();
  far_step<S, N, FIRST, BS>(acc, f0, da); far_step<S - 1, N, false, BS>(acc, f1, da); far_step<S, N, false, BS>(acc, f2, db); far_step<S - 1, N, false, BS>(acc, f3, db);
  asm volatile("wgmma.commit_group.sync.aligned;" ::: "memory");
}
__device__ __forceinline__ void mma16816bf(float* c, uint32_t a0, uint32_t a1, uint32_t a2, uint32_t a3, uint32_t b0, uint32_t b1) {
  asm volatile("mma.sync.aligned.m16n8k16.row.col.f32.bf16.bf16.f32 {%0,%1,%2,%3}, {%4,%5,%6,%7}, {%8,%9}, {%0,%1,%2,%3};"
    : "+f"(c[0]), "+f"(c[1]), "+f"(c[2]), "+f"(c[3]) : "r"(a0), "r"(a1), "r"(a2), "r"(a3), "r"(b0), "r"(b1));
}
__device__ __forceinline__ void mbar_wait(uint32_t bar, uint32_t parity) {
  uint32_t ok = 0; int it = 0;
  do {
    asm volatile("{.reg .pred p; mbarrier.try_wait.parity.shared::cta.b64 p, [%1], %2, 20000; selp.u32 %0, 1, 0, p;}" : "=r"(ok) : "r"(bar), "r"(parity) : "memory");
  } while (!ok && ++it < (1 << 16));
}
__device__ __forceinline__ void cexp2(float& r, float& i, float e, float x) {
  const float k = __fadd_rn(fmaf(x, 0.15915494309189535f, 12582912.f), -12582912.f);
  const float m = ex2(e), a = fmaf(k, -6.283185307179586f, x);
  r = m * fcos(a); i = m * fsin(a);
}
__device__ __forceinline__ void mma16816h(uint32_t* c, uint32_t a0, uint32_t a1, uint32_t a2, uint32_t a3, uint32_t b0, uint32_t b1) {
  asm("mma.sync.aligned.m16n8k16.row.col.f16.f16.f16.f16 {%0,%1}, {%2,%3,%4,%5}, {%6,%7}, {%0,%1};"
    : "+r"(c[0]), "+r"(c[1]) : "r"(a0), "r"(a1), "r"(a2), "r"(a3), "r"(b0), "r"(b1));
}
__device__ __forceinline__ float h_lo(uint32_t w) { return __half2float(__ushort_as_half((unsigned short)(w & 0xFFFFu))); }
__device__ __forceinline__ float h_hi(uint32_t w) { return __half2float(__ushort_as_half((unsigned short)(w >> 16))); }

__device__ __forceinline__ void load_E(uint32_t* E, uint32_t a0, uint32_t a1, uint32_t a2) {
  const uint4 e0 = lds128(a0), e1 = lds128(a1), e2 = lds128(a2);
  E[0] = e0.x; E[1] = e0.y; E[2] = e0.z; E[3] = e0.w; E[4] = e1.x; E[5] = e1.y; E[6] = e1.z; E[7] = e1.w; E[8] = e2.x; E[9] = e2.y; E[10] = e2.z; E[11] = e2.w;
}
template<bool FULL> __device__ __forceinline__ void build_V(const uint32_t* E, uint32_t o8, uint32_t o16, uint32_t o9) {
  uint32_t O[11], Q[11], R[10], V3[11], V5[10];
  #pragma unroll
  for (int n = FULL ? 3 : 4; n <= 10; n++) { O[n] = __byte_perm(E[n - 1], E[n], 0x5432); Q[n] = badd(O[n], E[n - 1]); }
  #pragma unroll
  for (int n = FULL ? 4 : 5; n <= (FULL ? 9 : 8); n++) R[n] = badd(Q[n], Q[n - 1]);
  #pragma unroll
  for (int n = FULL ? 4 : 7; n <= 10; n++) V3[n] = badd(Q[n], O[n - 1]);
  #pragma unroll
  for (int n = 5; n <= (FULL ? 9 : 8); n++) V5[n] = badd(E[n], R[n]);
  sts128(o8 + V3_OFF, V3[7], V3[8], V3[9], V3[10]);
  sts128(o8 + V5_OFF, V5[5], V5[6], V5[7], V5[8]);
  if (FULL) {
    sts128(o16 + V7_OFF, badd(R[6], V3[4]), badd(R[7], V3[5]), badd(R[8], V3[6]), badd(R[9], V3[7]));
    sts128(o9, badd(V5[6], R[4]), badd(V5[7], R[5]), badd(V5[8], R[6]), badd(V5[9], R[7]));
    sts128(o16 + V2_OFF, Q[7], Q[8], Q[9], Q[10]);
  }
}

__global__ void __cluster_dims__(2, 1, 1) __launch_bounds__(512, 1)
s4d_kernel(const __grid_constant__ Params P, const __grid_constant__ CUtensorMap tmU, const __grid_constant__ CUtensorMap tmO) {
  extern __shared__ __align__(256) uint8_t smem[];
  const int tid = threadIdx.x, lane = tid & 31, wi = __shfl_sync(0xFFFFFFFFu, tid >> 5, 0), wg = wi >> 2, wq = wi & 3;
  const int br = wq >> 1, hh = wq & 1;
  const unsigned pch = blockIdx.x * 4 + wg, pw = pch * 64 + hh * 32;
  const uint32_t wLA = __ldg(P.logA[br] + pw + lane), wAI = __ldg(P.Aim[br] + pw + lane);
  const uint32_t wDT = __ldg(P.logdt[br] + pch);
  const uint32_t wCR = __ldg(P.Cre[br] + pw + lane), wCI = __ldg(P.Cim[br] + pw + lane);
  const uint32_t wCR2 = __ldg(P.Cre[br] + (pw ^ 32) + lane), wCI2 = __ldg(P.Cim[br] + (pw ^ 32) + lane);
  const uint32_t wDS = __ldg(P.Dsk[br] + pch);
  unsigned epoch;
  asm volatile("ld.relaxed.gpu.global.u32 %0, [%1];" : "=r"(epoch) : "l"(P.epoch) : "memory");
  const uint32_t sb = (uint32_t)__cvta_generic_to_shared(smem);
  const int g = lane >> 2, q = lane & 3;
  const int rank = blockIdx.x & 1, clus = blockIdx.x >> 1;
  const uint32_t barU = sb + OFF_MISC, barY = sb + OFF_MISC + 8, junk = sb + OFF_MISC + 128;
  const bool gater = wg == 3;

  const uint32_t sT = sb + OFF_T + (wg * 2 + br) * T_BR;
  const uint32_t sU = sb + OFF_U1 + wg * U1_CH;
  const uint32_t sW = sb + OFF_W + wg * W_WG;
  const uint32_t sR = sW + wq * R_WARP;
  const uint32_t l4 = lane * 4, l16 = lane * 16;
  const uint32_t we = sR + l4, wo = sR + (l4 ^ 64);
  #pragma unroll
  for (int k = 0; k < 4; k++) sts128(sT + hh * CP + l16 + k * 512, 0, 0, 0, 0);
  if (lane < 10) {
    sts128(sU + wq * U1_PLANE + 1024 + l16, 0, 0, 0, 0);
    if (lane < 4) sts128(sT + hh * CP + 2048 + l16, 0, 0, 0, 0);
  }
  sts32(we + 48 * 128, 0x3C003C00u); sts32(we + 56 * 128, 0u);
  const bool lo = q < 2, fix = (hh == 0) && !(lane & 29);
  const uint32_t jk = sR + 2560, q64 = (lane & 1) * 64;
  const uint32_t c0 = sT + T_D + 606 - 256 * hh - l4 - 4 * q, p3 = sT + T_P3 + 190 - 32 * hh - 2 * g - q64;
  uint32_t tb0 = sT + T_D + 1116 - 256 * hh - l4;
  uint32_t tcl = lo ? c0 : jk + 2 + l4, tph = lo ? jk + l4 : p3;
  uint32_t tpa = lo ? sT + ((lane & 4) ? T_P7 + 126 : T_P9 + 128) - 16 * hh - (g & 6) - q64 : jk + l4;
  uint32_t tu2 = lo ? c0 - 4 : p3, tu4 = tu2 - (lo ? 128 : 16);
  uint32_t tu3 = tu4 + (lo ? 6 : (T_P5 - T_P3) + 2), tu1 = fix ? jk : tu2 + (lo ? 6 : (T_P5 - T_P3) + 2);
  uint32_t tcf = fix ? jk + 2 : tcl, tphf = fix ? jk : tph, tpaf = fix ? jk : tpa;
  const int rw = (lane & 7) - 4 * rank;
  uint32_t xdst = sb + OFF_U1 + (63 - 8 * ((wi - 4) & 7)) * 16 + (lane >> 3) * U1_PLANE + rw * U1_CH;
  if ((unsigned)rw >= 4u) xdst = junk + 128 + (xdst & 127u);
  const uint32_t xsrc = sb + OFF_RAW + ((wi - 4) & 7) * 4096 + l16;
  uint32_t gL = sT - 32 * hh + ((lane & 4) ? 0 : CP + 2) - 2 * g + 4 * q;
  const int role = (wq + wg) & 3;
  uint32_t ve2 = sU + (63 - 8 * role) * 16 + q * U1_PLANE - g * 16;
  uint32_t ve1 = ve2 + (q == 0 ? 3 * U1_PLANE + 16 : -U1_PLANE), ve0 = ve2 + (lo ? 2 * U1_PLANE + 16 : -2 * U1_PLANE);
  const uint32_t vo8 = sW + (5 - role) * 512 + l16;
  uint32_t vo16 = sW + (1 - (role >> 1)) * 1024 + (role & 1) * 256 + q64 * 8 + (lane >> 1) * 16;
  uint32_t vo9 = vo16 + V9_OFF + ((lane & 1) ? 16 - 512 : 512);
  if (lane == 31 && (role & 1)) vo9 = (role == 3) ? junk : sW + V9_OFF;
  keep(ve0); keep(ve1); keep(ve2); keep(vo16); keep(vo9);
  keep(tb0); keep(tcl); keep(tph); keep(tpa); keep(tu1); keep(tu2); keep(tu3); keep(tu4); keep(tcf); keep(tphf); keep(tpaf); keep(xdst); keep(gL);

  asm volatile("fence.proxy.async.shared::cta;" ::: "memory");
  __syncwarp();
  if (lane == 0 && gater) {
    asm volatile("cp.async.bulk.global.shared::cta.bulk_group [%0], [%1], 2048;" :: "l"(P.out + (size_t)(blockIdx.x * 16 + wq * 4) * 64), "r"(sT + hh * CP) : "memory");
    asm volatile("cp.async.bulk.global.shared::cta.bulk_group [%0], [%1], 2048;" :: "l"(P.out + (size_t)(blockIdx.x * 16 + wq * 4 + 2) * 64), "r"(sT + hh * CP) : "memory");
    asm volatile("cp.async.bulk.commit_group;" ::: "memory");
  }
  if (tid == 480) {
    asm volatile("prefetch.tensormap [%0];" :: "l"(&tmU) : "memory");
    asm volatile("prefetch.tensormap [%0];" :: "l"(&tmO) : "memory");
    asm volatile("mbarrier.init.shared::cta.b64 [%0], 1;" :: "r"(barU) : "memory");
    asm volatile("mbarrier.init.shared::cta.b64 [%0], 8;" :: "r"(barU + 40) : "memory");
    asm volatile("mbarrier.init.shared::cta.b64 [%0], 17;" :: "r"(barY + 24) : "memory");
    asm volatile("mbarrier.init.shared::cta.b64 [%0], 17;" :: "r"(barY + 40) : "memory");
    asm volatile("mbarrier.arrive.expect_tx.shared::cta.b64 _, [%0], %1;" :: "r"(barY + 40), "r"(4096) : "memory");
    asm volatile("mbarrier.init.shared::cta.b64 [%0], 5;" :: "r"(barY) : "memory");
    asm volatile("mbarrier.init.shared::cta.b64 [%0], 17;" :: "r"(barY + 8) : "memory");
    asm volatile("mbarrier.init.shared::cta.b64 [%0], 17;" :: "r"(barY + 16) : "memory");
    asm volatile("mbarrier.arrive.expect_tx.shared::cta.b64 _, [%0], %1;" :: "r"(barU), "r"(32768) : "memory");
    asm volatile("mbarrier.arrive.expect_tx.shared::cta.b64 _, [%0], %1;" :: "r"(barY), "r"(12 * Y_BLK) : "memory");
    asm volatile("mbarrier.arrive.expect_tx.shared::cta.b64 _, [%0], %1;" :: "r"(barY + 8), "r"(4096) : "memory");
    asm volatile("mbarrier.arrive.expect_tx.shared::cta.b64 _, [%0], %1;" :: "r"(barY + 16), "r"(4096) : "memory");
    asm volatile("mbarrier.arrive.expect_tx.shared::cta.b64 _, [%0], %1;" :: "r"(barY + 24), "r"(4096) : "memory");
    asm volatile("fence.mbarrier_init.release.cluster;" ::: "memory");
  }
  __syncwarp();
  asm volatile("barrier.cluster.arrive.relaxed.aligned;" ::: "memory");
  if (wi == 15) {
    asm volatile("barrier.cluster.wait.aligned;" ::: "memory");
    if (lane == 0) {
      #pragma unroll
      for (int k = 0; k < 4; k++)
        asm volatile("cp.async.bulk.tensor.2d.shared::cluster.global.mbarrier::complete_tx::bytes.multicast::cluster [%0], [%1, {%3, %4}], [%2], %5;"
          :: "r"(sb + OFF_RAW + (rank * 1024 + k * 256) * 16), "l"(&tmU), "r"(barU), "r"(clus * 8), "r"(rank * 1024 + k * 256), "h"((unsigned short)3) : "memory");
    }
    __syncwarp();
  }

  const float dt = bf_lo(pk_bf(ex2(bf_lo(wDT) * 1.4426950408889634f), 0.f));
  float csc, tsc;
  {
    uint32_t m = __vmaxu2(__vmaxu2(wCR & 0x7FFF7FFFu, wCI & 0x7FFF7FFFu), __vmaxu2(wCR2 & 0x7FFF7FFFu, wCI2 & 0x7FFF7FFFu));
    m = max(m & 0xFFFFu, m >> 16);
    m = __reduce_max_sync(0xFFFFFFFFu, m);
    int k = 134 - (int)(m >> 7);
    k = min(max(k, -126), 126);
    csc = __uint_as_float((uint32_t)(k + 127) << 23);
    tsc = 2.0f * dt * __uint_as_float((uint32_t)(127 - k) << 23);
  }
  {
    const uint32_t Ab = pk_bf(ex2(bf_lo(wLA) * 1.4426950408889634f), ex2(bf_hi(wLA) * 1.4426950408889634f));
    const float ndt = dt * -1.4426950408889634f;
    const float ea = bf_lo(Ab) * ndt, eb = bf_hi(Ab) * ndt, ta = bf_lo(wAI) * dt, tb = bf_hi(wAI) * dt;
    float ra, ia, rb, ib;
    cexp2(ra, ia, ea, ta); cexp2(rb, ib, eb, tb);
#define PK1 C2{pk_h(ra, rb), pk_h(ia, ib)}
#define SQ1 csq(ra, ia); csq(rb, ib);
#define PUT(T, G, V) { sts32(((G) & 1 ? wo : we) + ((T) * 16 + (G)) * 128, (V).r); sts32(((G) & 1 ? wo : we) + ((T) * 16 + 8 + (G)) * 128, (V).i); }
    C2 H0[8], X[8], H1[8], H2[5];
    H0[0] = C2{pk_h(bf_lo(wCR) * csc, bf_hi(wCR) * csc), pk_h(bf_lo(wCI) * -csc, bf_hi(wCI) * -csc)}; PUT(0, 0, H0[0])
    const C2 m1 = PK1; H0[1] = cmulc(H0[0], m1); PUT(0, 1, H0[1])
    SQ1 const C2 m2 = PK1;
    H0[2] = cmulc(H0[0], m2); PUT(0, 2, H0[2]) H0[3] = cmulc(H0[1], m2); PUT(0, 3, H0[3])
    SQ1 const C2 m4 = PK1;
    H0[4] = cmulc(H0[0], m4); PUT(0, 4, H0[4]) H0[5] = cmulc(H0[1], m4); PUT(0, 5, H0[5])
    SQ1 X[1] = PK1; PUT(3, 1, X[1])
    H0[6] = cmulc(H0[2], m4); PUT(0, 6, H0[6]) H0[7] = cmulc(H0[3], m4); PUT(0, 7, H0[7])
    SQ1 X[2] = PK1; PUT(3, 2, X[2])
    X[3] = cmul(X[2], X[1]); PUT(3, 3, X[3])
    SQ1 X[4] = PK1; PUT(3, 4, X[4])
    X[5] = cmul(X[4], X[1]); PUT(3, 5, X[5]) X[6] = cmul(X[4], X[2]); PUT(3, 6, X[6])
    SQ1 const C2 Z = PK1;
    sts32(we + 64 * 128, Z.r); sts32(we + 65 * 128, Z.i);
    X[7] = cmul(X[6], X[1]); PUT(3, 7, X[7])
    SQ1 SQ1 const C2 m256 = PK1;
    H1[0] = cmulc(H0[0], m256); PUT(1, 0, H1[0]) H1[1] = cmulc(H0[2], m256); PUT(1, 1, H1[1])
    SQ1 const C2 m512 = PK1;
    H1[2] = cmulc(H0[4], m256); PUT(1, 2, H1[2]) H1[3] = cmulc(H0[6], m256); PUT(1, 3, H1[3])
    SQ1 const C2 m1k = PK1;
    H1[4] = cmulc(H0[0], m512); PUT(1, 4, H1[4]) H1[5] = cmulc(H0[4], m512); PUT(1, 5, H1[5])
    H1[6] = cmulc(H1[0], m512); PUT(1, 6, H1[6]) H1[7] = cmulc(H1[2], m512); PUT(1, 7, H1[7])
    H2[0] = cmulc(H0[0], m1k); PUT(2, 0, H2[0]) H2[1] = cmulc(H1[0], m1k); PUT(2, 1, H2[1])
    H2[2] = cmulc(H1[4], m1k); PUT(2, 2, H2[2]) H2[3] = cmulc(H1[6], m1k); PUT(2, 3, H2[3])
    H2[4] = cmulc(H2[0], m1k); PUT(2, 4, H2[4])
#undef PUT
#undef PK1
#undef SQ1
  }
  if (wi != 15) asm volatile("barrier.cluster.wait.aligned;" ::: "memory");
  __syncwarp();
  uint32_t cD[2][3][2];
  #pragma unroll
  for (int i = 0; i < 12; i++) (&cD[0][0][0])[i] = 0u;
  {
    #pragma unroll
    for (int h2 = 0; h2 < 2; h2++) {
      const uint32_t r0 = sR + g * 128 + 16 * ((q + 4 * h2) ^ (4 * (g & 1))), zb = sR + 64 * 128 + 16 * (q + 4 * h2);
      const uint4 Xr = lds128(r0 + 48 * 128), Xi = lds128(r0 + 56 * 128), Zr = lds128(zb), Zi = lds128(zb + 128);
      const uint4 H0r = lds128(r0), H0i = lds128(r0 + 8 * 128), H1r = lds128(r0 + 16 * 128), H1i = lds128(r0 + 24 * 128);
      const uint4 H2r = lds128(r0 + 32 * 128), H2i = lds128(r0 + 40 * 128);
#define KSTEP(E, F) { \
      const C2 za = C2{Zr.E, Zi.E}, zc = C2{Zr.F, Zi.F}, a0 = C2{Xr.E, Xi.E}, c0 = C2{Xr.F, Xi.F}; \
      const C2 a1 = cmul(a0, za), c1 = cmul(c0, zc), a2 = cmul(a1, za), c2 = cmul(c1, zc), a3 = cmul(a2, za), c3 = cmul(c2, zc); \
      mma16816h(cD[0][0], a0.r, a1.r, c0.r, c1.r, H0r.E, H0r.F); mma16816h(cD[0][1], a0.r, a1.r, c0.r, c1.r, H1r.E, H1r.F); \
      mma16816h(cD[0][2], a0.r, a1.r, c0.r, c1.r, H2r.E, H2r.F); \
      mma16816h(cD[0][0], a0.i, a1.i, c0.i, c1.i, H0i.E, H0i.F); mma16816h(cD[0][1], a0.i, a1.i, c0.i, c1.i, H1i.E, H1i.F); \
      mma16816h(cD[0][2], a0.i, a1.i, c0.i, c1.i, H2i.E, H2i.F); \
      mma16816h(cD[1][0], a2.r, a3.r, c2.r, c3.r, H0r.E, H0r.F); mma16816h(cD[1][1], a2.r, a3.r, c2.r, c3.r, H1r.E, H1r.F); \
      mma16816h(cD[1][2], a2.r, a3.r, c2.r, c3.r, H2r.E, H2r.F); \
      mma16816h(cD[1][0], a2.i, a3.i, c2.i, c3.i, H0i.E, H0i.F); mma16816h(cD[1][1], a2.i, a3.i, c2.i, c3.i, H1i.E, H1i.F); \
      mma16816h(cD[1][2], a2.i, a3.i, c2.i, c3.i, H2i.E, H2i.F); }
      KSTEP(x, y) KSTEP(z, w)
#undef KSTEP
    }
  }
  __syncwarp();
  uint4 gx[8], gw0, gw1;
  if (gater) {
    const size_t grow = (size_t)(blockIdx.x * 16 + wq * 4) * 64 + lane;
    #pragma unroll
    for (int r = 0; r < 8; r++) gx[r] = __ldg(P.u + grow + r * 32);
    gw0 = __ldg(P.gw + lane); gw1 = __ldg(P.gw + 32 + lane);
    if (lane == 0) asm volatile("cp.async.bulk.wait_group 0;" ::: "memory");
    __syncwarp();
  } else if (wg) {
    mbar_wait(barU, 0);
    #pragma unroll
    for (int k = 0; k < 8; k += 4) {
      uint32_t r[4][4];
      #pragma unroll
      for (int j = 0; j < 4; j++) ldsm4t(r[j][0], r[j][1], r[j][2], r[j][3], xsrc + (k + j) * 512);
      #pragma unroll
      for (int j = 0; j < 4; j++) stsm4(xdst - 16 * (k + j), r[j][0], r[j][1], r[j][2], r[j][3]);
    }
    asm volatile("fence.proxy.async.shared::cta;" ::: "memory");
    __syncwarp();
    if (lane == 0) asm volatile("mbarrier.arrive.shared::cta.b64 _, [%0];" :: "r"(barU + 40) : "memory");
  }
  asm volatile("barrier.cluster.arrive.relaxed.aligned;" ::: "memory");
  float v[12];
  {
    const uint32_t sO = sW + (wq ^ 1) * R_WARP + lane * 16, sS = sR + lane * 16;
#define XCH(SND, KEEP) \
    sts128(sS, cD[SND][0][0], cD[SND][0][1], cD[SND][1][0], cD[SND][1][1]); sts128(sS + 512, cD[SND][2][0], cD[SND][2][1], 0u, 0u); \
    bar_sync(1 + wg * 2 + br, 64); \
    { const uint4 o = lds128(sO), p = lds128(sO + 512); const uint32_t w[6] = {o.x, o.y, o.z, o.w, p.x, p.y}; \
      _Pragma("unroll") for (int k = 0; k < 6; k++) { \
        v[2 * k] = (h_lo(cD[KEEP][k >> 1][k & 1]) + h_lo(w[k])) * tsc; v[2 * k + 1] = (h_hi(cD[KEEP][k >> 1][k & 1]) + h_hi(w[k])) * tsc; } }
    if (hh) { XCH(0, 1) } else { XCH(1, 0) }
#undef XCH
  }
  uint32_t w1f = 0, w2f = 0;
  {
    if (hh == 0 && lane == 0) v[0] += bf_lo(wDS);
    #pragma unroll
    for (int a = 0; a < 2; a++) {
      const uint32_t w0 = pk_bf(v[2 * a + 1], v[2 * a]);
      sts32(tb0 - 128 * a, w0);
      sts16(tb0 - 128 * a + CP + 4, w0 >> 16);
      sts16(tb0 - 128 * a + CP + 2, w0);
      const uint32_t w1 = pk_bf(v[4 + 2 * a], v[5 + 2 * a]);
      const uint32_t aa = __byte_perm(w1, 0, 0x1010), ba = __byte_perm(w1, 0, 0x1032);
      sts16(a ? tu3 : tu1, w1);
      sts16(a ? tu4 : tu2, ba);
      const uint32_t w2 = pk_bf(v[8 + 2 * a], v[9 + 2 * a]);
      sts32(tcl - 128 * a - 2, aa);
      sts32((a ? tcl : tcf) - 128 * a + CP + 2, aa);
      sts32(tcl - 128 * a + CP - 2, ba);
      sts16((a ? tph : tphf) - 16 * a + T_P5 - T_P3 + CP + 4, w1);
      sts16(tph - 16 * a + CP + 2, ba);
      sts16((a ? tpa : tpaf) - 8 * a, w2); sts16((a ? tpa : tpaf) - 8 * a + CP + 2, w2);
      sts16(tpa - 8 * a - 32, w2 >> 16); sts16(tpa - 8 * a - 32 + CP + 2, w2 >> 16);
      if (a == 0) { w1f = aa; w2f = w2; }
    }
    if (fix) {
      if (q == 0) {
        sts16(sT + T_D + CP + 2 * (560 - 256), w1f);
        sts16(sT + T_P5 + 64, w2f); sts16(sT + T_P5 + CP + 66, w2f);
      } else {
        sts32(sT + T_D + 92, w1f); sts16(sT + T_D + 96, w1f); sts16(sT + T_D + 90, w1f);
        sts32(sT + T_D + CP + 96, w1f); sts32(sT + T_D + CP + 92, w1f);
        sts16(sT + T_P9, w2f); sts16(sT + T_P9 + CP + 2, w2f);
      }
    }
  }

  if (gater) {
    float s01[4] = {0.f, 0.f, 0.f, 0.f}, s23[4] = {0.f, 0.f, 0.f, 0.f};
    const uint32_t one = 0x3F803F80u;
#define GMMA(S, A, B, W) mma16816bf(S, bmul(A.x, W.x), bmul(B.x, W.x), bmul(A.y, W.y), bmul(B.y, W.y), one, one); \
                         mma16816bf(S, bmul(A.z, W.z), bmul(B.z, W.z), bmul(A.w, W.w), bmul(B.w, W.w), one, one);
    GMMA(s01, gx[0], gx[2], gw0) GMMA(s23, gx[4], gx[6], gw0) GMMA(s01, gx[1], gx[3], gw1) GMMA(s23, gx[5], gx[7], gw1)
#undef GMMA
    float s = (q & 2) ? ((q & 1) ? s23[2] : s23[0]) : ((q & 1) ? s01[2] : s01[0]);
    s += __shfl_xor_sync(0xFFFFFFFFu, s, 4); s += __shfl_xor_sync(0xFFFFFFFFu, s, 8); s += __shfl_xor_sync(0xFFFFFFFFu, s, 16);
    s = bf_lo(pk_bf(s, 0.f));
    const float gv = __fdividef(1.0f, 1.0f + ex2(s * -1.4426950408889634f));
    const uint32_t gpub = ((epoch + 1) << 16) | (pk_bf(gv, 0.f) & 0xFFFFu);
    if (lane < 4) asm volatile("st.relaxed.gpu.global.u32 [%0], %1;" :: "l"(P.gate + blockIdx.x * 16 + wq * 4 + lane), "r"(gpub) : "memory");
  }
  mbar_wait(barU + 40, 0);
  bar_sync(9 + wg, 128);
  const uint32_t g3 = gL + T_P3 + 190, g5 = gL + T_P5 + 190, g7 = gL + T_P7 + 126, g9 = gL + T_P9 + 126, gD = gL + T_D + 1118;
  const uint32_t sV = sW;
#define PK4(A, B) pk_bf(A[4 * (B)], A[4 * (B) + 1]), pk_bf(A[4 * (B) + 2], A[4 * (B) + 3]), pk_bf(A[4 * (B) + 4], A[4 * (B) + 5]), pk_bf(A[4 * (B) + 6], A[4 * (B) + 7])
#define PUSHV(V, DST, BAR) \
    asm volatile("st.async.shared::cluster.mbarrier::complete_tx::bytes.v4.b32 [%0], {%1,%2,%3,%4}, [%5];" \
      :: "r"(mapa(DST, rank ^ 1)), "r"(V.x), "r"(V.y), "r"(V.z), "r"(V.w), "r"(mapa(BAR, rank ^ 1)) : "memory");
#define ARRIVE(BAR) if ((tid_now() & 31) == 0) asm volatile("mbarrier.arrive.shared::cta.b64 _, [%0];" :: "r"(BAR) : "memory");

  float acc1[32], accA[24], accB[16], accS[16], accT[8];
  uint32_t raw[10];
  const uint64_t dU = mkdesc(sU, U1_PLANE, 128);
  raw_load<7>(raw, gD, -2);
  {
    uint32_t E[12], E2[12];
    load_E(E, ve0, ve1, ve2);
    if (role < 2) load_E(E2, ve0 - 512, ve1 - 512, ve2 - 512);
    dense_group<-1, 3, 2>(acc1, raw, dU);
    dense_load<2, 3>(raw, gD);
    build_V<true>(E, vo8, vo16, vo9);
    if (role < 2) build_V<false>(E2, vo8 - 2048, 0, 0);
    else {
      sts128(sV + l16 + (role & 1) * V5_OFF + 3072, 0, 0, 0, 0);
      if (role == 3 && lane == 0) sts128(sV + V9_OFF + 1024, 0, 0, 0, 0);
    }
  }
  dense_group<2, 3, 2>(acc1, raw, dU);
  dense_load<5, 3>(raw, gD);
  dense_group<5, 3, 2>(acc1, raw, dU);
  dense_load<8, 3>(raw, gD);
  asm volatile("fence.proxy.async.shared::cta;" ::: "memory");
  dense_group<8, 3, 2>(acc1, raw, dU);
  dense_load<11, 2>(raw, gD);
  dense_group<11, 2, 2>(acc1, raw, dU);
  dense_load<13, 2>(raw, gD);
  dense_group<13, 2, 2>(acc1, raw, dU);
  dense_load<15, 3>(raw, gD);
  wg_wait<0>();
  redef<28>(acc1);
  dense_group<15, 3, 2>(acc1, raw, dU);
  dense_load<18, 3>(raw, gD);
  dense_group<18, 3, 2>(acc1, raw, dU);
  dense_load<21, 3>(raw, gD);
  bar_sync(9 + wg, 128);
  dense_group<21, 3, 2>(acc1, raw, dU);
  dense_load<24, 3>(raw, gD);
  dense_group<24, 3, 2>(acc1, raw, dU);
  dense_load<27, 3>(raw, gD);
  unsigned long long gv;
  asm volatile("ld.relaxed.gpu.global.b64 %0, [%1];" : "=l"(gv) : "l"(P.gate + wg * 512 + rank * 256 + 2 * (tid_now() & 127)) : "memory");
  dense_group<27, 3, 2>(acc1, raw, dU);
  dense_load<30, 2>(raw, gD);
  dense_group<30, 2, 2>(acc1, raw, dU);
  dense_load<32, 2>(raw, gD);
  dense_group<32, 2, 1>(acc1, raw, dU);

  const uint64_t d3 = mkdesc(sV + V3_OFF, 128, 512), d5 = mkdesc(sV + V5_OFF, 128, 512);
  const uint64_t d7 = mkdesc(sV + V7_OFF, 128, 512), d9 = mkdesc(sV + V9_OFF, 128, 512), d2 = mkdesc(sV + V2_OFF, 128, 512);
  uint32_t rb[10];
  raw_load<5>(raw, g3, -2); raw_load<5>(raw + 5, g5, -2);
  raw_load<4>(rb + 1, g3, 3); raw_load<4>(rb + 6, g5, 3);
  rb[0] = cpy(raw[4]); rb[5] = cpy(raw[9]);
  far_group<1, 48, true>(accA, raw, d3, d5);
  far_group<-1, 48>(accA, rb, d3, d5);
  wg_wait<2>();
  fence_regs<32>(acc1);
  uint32_t sF, uF, sS3;
  {
    const int ln = tid_now(), mat = (ln >> 3) & 3, r8 = ln & 7;
    const uint32_t uo = (br * 4 + 2 * hh + (mat & 1)) * Y_PLANE + r8 * 16;
    const uint32_t sY = sW + Y_OFF + (1 - (mat >> 1)) * Y_OWN + uo;
    stsm4t(sY, PK4(acc1, 6));
    asm volatile("barrier.cluster.wait.aligned;" ::: "memory");
    __syncwarp();
    stsm4t(sY + 3 * Y_BLK, PK4(acc1, 0)); stsm4t(sY + 2 * Y_BLK, PK4(acc1, 2)); stsm4t(sY + Y_BLK, PK4(acc1, 4));
    {
      const uint4 v = lds128(sW + Y_OFF + (rank ^ 1) * Y_OWN + uo);
      if ((ln & 16) == 0) PUSHV(v, sb + OFF_RAW + wg * Y_OWN + uo, barY + 40)
      ARRIVE(barY + 40)
    }
    raw_load<5>(raw, g3, 6); raw_load<5>(raw + 5, g5, 6);
    far_group<-3, 32, true>(accB, raw, d3, d5);
    asm volatile("fence.proxy.async.shared::cta;" ::: "memory");
    bar_sync(9 + wg, 128);
    if ((ln & 127) == 0) {
      asm volatile("cp.async.bulk.shared::cluster.shared::cta.mbarrier::complete_tx::bytes [%0], [%1], %2, [%3];"
        :: "r"(mapa(sb + OFF_RAW + wg * Y_OWN + Y_BLK, rank ^ 1)), "r"(sW + Y_OFF + (rank ^ 1) * Y_OWN + Y_BLK), "r"(3 * Y_BLK), "r"(mapa(barY, rank ^ 1)) : "memory");
      asm volatile("mbarrier.arrive.shared::cta.b64 _, [%0];" :: "r"(barY) : "memory");
    }
    uF = (br * 4 + (r8 & 3)) * Y_PLANE + (7 - 4 * hh - 2 * (mat & 1) - (r8 >> 2)) * 16;
    sF = sW + F_OFF + (1 - (mat >> 1)) * F_OWN + uF;
    sS3 = (br * 4 + 2 * (r8 & 1) + (mat >> 1)) * Y_PLANE + (7 - 4 * (mat & 1) - (r8 >> 1)) * 16;
  }
  {
    const unsigned tag = (epoch + 1) & 0xFFFFu;
    int it = 0;
    while (((((uint32_t)gv >> 16) != tag) || (((uint32_t)(gv >> 48)) != tag)) && ++it < (1 << 20))
      asm volatile("ld.relaxed.gpu.global.b64 %0, [%1];" : "=l"(gv) : "l"(P.gate + wg * 512 + rank * 256 + 2 * (tid_now() & 127)) : "memory");
  }
  const uint32_t g2 = __byte_perm((uint32_t)gv, (uint32_t)(gv >> 32), 0x5410);
  auto finalize = [&]() {
    uint32_t ya[8], yb[8], f0, f1, ft0, ft1;
    uint4* dst;
    const int tx = tid_now() & 127;
    const uint32_t off = wg * Y_BLK + ((tx >> 2) & 3) * Y_PLANE + (7 - (tx >> 4)) * 16 + (tx & 3) * 4;
    const uint32_t own = sb + OFF_W + Y_OFF + rank * Y_OWN + off, oth = sb + OFF_RAW + off;
    const uint32_t a0 = rank ? oth : own, a1 = rank ? own : oth;
    const uint32_t st0 = rank ? Y_OWN : W_WG, st1 = rank ? W_WG : Y_OWN;
    const uint32_t fown = sb + OFF_W + F_OFF + rank * F_OWN + off, foth = (wg == 1) ? oth + 4 * Y_OWN - Y_BLK : oth + (OFF_FIN - OFF_RAW) - 2 * Y_BLK;
    const uint32_t fst = (wg == 1) ? Y_BLK : 2 * Y_BLK;
    f0 = rank ? foth : fown; f1 = rank ? fown : foth; ft0 = rank ? fst : W_WG; ft1 = rank ? W_WG : fst;
    dst = P.out + (size_t)(wg * 512 + rank * 256 + 2 * tx) * 64 + clus;
    mbar_wait(wg ? barY : barY + 40, 0);
    #pragma unroll
    for (int c = 0; c < 4; c++) {
      ya[c] = lds32(a0 + c * st0); yb[c] = lds32(a0 + c * st0 + 4 * Y_PLANE);
      ya[4 + c] = lds32(a1 + c * st1); yb[4 + c] = lds32(a1 + c * st1 + 4 * Y_PLANE);
    }
    if (wg) {
      mbar_wait(barY + 8 * wg, 0);
      #pragma unroll
      for (int c = 0; c < 4; c++) {
        ya[c] = badd(ya[c], lds32(f0 + c * ft0)); yb[c] = badd(yb[c], lds32(f0 + c * ft0 + 4 * Y_PLANE));
        ya[4 + c] = badd(ya[4 + c], lds32(f1 + c * ft1)); yb[4 + c] = badd(yb[4 + c], lds32(f1 + c * ft1 + 4 * Y_PLANE));
      }
    }
    const uint32_t og = bsub(0x3F803F80u, g2);
    uint32_t o[8];
    #pragma unroll
    for (int c = 0; c < 8; c++) o[c] = badd(bmul(g2, ya[c]), bmul(og, yb[c]));
    if (wg == 0) {
      const uint32_t stg = sb + OFF_U1 + wi * 1024, sw = tx & 4;
      const uint32_t s0 = sw ? 0x7632 : 0x5410, s1 = sw ? 0x5410 : 0x7632, ad = stg + (tx & 31) * 32 + sw * 4;
      sts128(ad, __byte_perm(o[0], o[1], s0), __byte_perm(o[2], o[3], s0), __byte_perm(o[4], o[5], s0), __byte_perm(o[6], o[7], s0));
      sts128(ad ^ 16, __byte_perm(o[0], o[1], s1), __byte_perm(o[2], o[3], s1), __byte_perm(o[4], o[5], s1), __byte_perm(o[6], o[7], s1));
      asm volatile("fence.proxy.async.shared::cta;" ::: "memory");
      __syncwarp();
      if ((tx & 31) == 0) {
        asm volatile("cp.reduce.async.bulk.tensor.2d.global.shared::cta.add.tile.bulk_group [%0, {%2, %3}], [%1];"
          :: "l"(&tmO), "r"(stg), "r"(clus * 8), "r"(wg * 512 + rank * 256 + wq * 64) : "memory");
        asm volatile("cp.async.bulk.commit_group;" ::: "memory");
      }
    } else {
      asm volatile("red.global.add.noftz.v4.bf16x2 [%0], {%1,%2,%3,%4};" :: "l"(dst),
      "r"(__byte_perm(o[0], o[1], 0x5410)), "r"(__byte_perm(o[2], o[3], 0x5410)), "r"(__byte_perm(o[4], o[5], 0x5410)), "r"(__byte_perm(o[6], o[7], 0x5410)) : "memory");
      asm volatile("red.global.add.noftz.v4.bf16x2 [%0], {%1,%2,%3,%4};" :: "l"(dst + 64),
      "r"(__byte_perm(o[0], o[1], 0x7632)), "r"(__byte_perm(o[2], o[3], 0x7632)), "r"(__byte_perm(o[4], o[5], 0x7632)), "r"(__byte_perm(o[6], o[7], 0x7632)) : "memory");
    }
  };
  if (wg == 0) finalize();
  wg_wait<1>();
  fence_regs<24>(accA);
  raw_load<5>(raw, g7, -2); raw_load<5>(raw + 5, g9, -2);
  rb[0] = cpy(raw[4]); rb[5] = cpy(raw[9]);
  const uint32_t f1k = lds32(sT + T_P5 + 64);
  stsm4(sF + Y_BLK, PK4(accA, 4));
  {
    const int ln = tid_now() & 31, df = (ln >> 2) - 2 * (ln & 3);
    const uint32_t b = f1k & 0xFFFFu, dg = (df == 0) ? b : ((df == 1) ? (b << 16) : 0u);
    const Frag f0 = mkfrag(raw, true), f1 = mkfrag(raw + 2, false), f2 = mkfrag(raw + 5, true), f3 = mkfrag(raw + 7, false);
    Frag f4, f5;
    f4.a0 = cpy(hh ? 0u : dg); f4.a1 = cpy(0u); f4.a2 = cpy(0u); f4.a3 = cpy(f4.a0);
    f5.a0 = cpy(hh ? dg : 0u); f5.a1 = cpy(0u); f5.a2 = cpy(0u); f5.a3 = cpy(f5.a0);
    wg_fence();
    far_step<1, 32, true, 1024>(accS, f0, d7); far_step<0, 32, false, 1024>(accS, f1, d7);
    far_step<1, 32, false, 1024>(accS, f2, d9); far_step<0, 32, false, 1024>(accS, f3, d9);
    far_step<0, 32>(accS, f4, d2); far_step<1, 32>(accS, f5, d2);
    asm volatile("wgmma.commit_group.sync.aligned;" ::: "memory");
  }
  __syncwarp();
  {
    const uint4 v = lds128(sW + F_OFF + (rank ^ 1) * F_OWN + Y_BLK + uF);
    if ((tid_now() & 16) == 0) PUSHV(v, sb + OFF_RAW + 4 * Y_OWN + wg * Y_BLK + uF, barY + 8)
    ARRIVE(barY + 8)
  }
  wg_wait<1>();
  raw_load<4>(rb + 1, g7, 3); raw_load<4>(rb + 6, g9, 3);
  far_group<-1, 16, true, 1024>(accT, rb, d7, d9);
  fence_regs<16>(accB);
  #pragma unroll
  for (int i = 0; i < 16; i++) accA[i] += accB[i];
  stsm4(sF + 3 * Y_BLK, PK4(accA, 0)); stsm4(sF + 2 * Y_BLK, PK4(accA, 2));
  bar_sync(1 + wg * 2 + br, 64);
  uint32_t fp[8];
  const uint32_t aS3 = sW + F_OFF + hh * F_OWN + sS3;
  ldsm4(fp[0], fp[1], fp[2], fp[3], aS3 + 3 * Y_BLK); ldsm4(fp[4], fp[5], fp[6], fp[7], aS3 + 2 * Y_BLK);
  wg_wait<1>();
  fence_regs<16>(accS);
  #pragma unroll
  for (int i = 4; i < 8; i++) { accS[2 * i] += bf_lo(fp[i]); accS[2 * i + 1] += bf_hi(fp[i]); }
  stsm4(aS3 + 2 * Y_BLK, PK4(accS, 2));
  __syncwarp();
  if (hh != rank) { const uint4 v = lds128(aS3 + 2 * Y_BLK); PUSHV(v, sb + OFF_FIN + wg * 2 * Y_BLK + sS3, barY + 16) }
  ARRIVE(barY + 16)
  #pragma unroll
  for (int i = 0; i < 4; i++) { accS[2 * i] += bf_lo(fp[i]); accS[2 * i + 1] += bf_hi(fp[i]); }
  wg_wait<0>();
  fence_regs<8>(accT);
  #pragma unroll
  for (int i = 0; i < 8; i++) accS[i] += accT[i];
  stsm4(aS3 + 3 * Y_BLK, PK4(accS, 0));
  __syncwarp();
  if (hh != rank) { const uint4 v = lds128(aS3 + 3 * Y_BLK); PUSHV(v, sb + OFF_FIN + wg * 2 * Y_BLK + Y_BLK + sS3, barY + 24) }
  ARRIVE(barY + 24)
  if (wg != 0) finalize();
  if (wg == 0 && (tid_now() & 31) == 0) asm volatile("cp.async.bulk.wait_group.read 0;" ::: "memory");
  __syncwarp();
  asm volatile("barrier.cluster.arrive.relaxed.aligned;" ::: "memory");
#undef PK4
#undef PUSHV
#undef ARRIVE
  asm volatile("barrier.cluster.wait.aligned;" ::: "memory");
  if (blockIdx.x == 0 && tid_now() == 0) *P.epoch = epoch + 1;
}

typedef CUresult (*EncodeFn)(CUtensorMap*, CUtensorMapDataType, cuuint32_t, void*, const cuuint64_t*, const cuuint64_t*, const cuuint32_t*,
                             const cuuint32_t*, CUtensorMapInterleave, CUtensorMapSwizzle, CUtensorMapL2promotion, CUtensorMapFloatOOBfill);

}

extern "C" void kernel_launch(void* const* d_in, const int* in_sizes, int n_in, void* d_out, int out_size) {
  static EncodeFn enc = nullptr;
  static unsigned *gate_ptr = nullptr, *epoch_ptr = nullptr;
  if (!enc) {
    cudaGetSymbolAddress((void**)&gate_ptr, g_gate);
    cudaGetSymbolAddress((void**)&epoch_ptr, g_epoch);
    cudaFuncSetAttribute(s4d_kernel, cudaFuncAttributeMaxDynamicSharedMemorySize, SMEM_BYTES);
    void* fn = nullptr; cudaDriverEntryPointQueryResult qr;
    cudaGetDriverEntryPoint("cuTensorMapEncodeTiled", &fn, cudaEnableDefault, &qr);
    enc = (EncodeFn)fn;
  }
  CUtensorMap tm, tmo;
  {
    cuuint64_t gd[2] = {512, 2048}; cuuint64_t gs[1] = {1024}; cuuint32_t box[2] = {8, 256}; cuuint32_t es[2] = {1, 1};
    enc(&tm, CU_TENSOR_MAP_DATA_TYPE_BFLOAT16, 2, d_in[0], gd, gs, box, es, CU_TENSOR_MAP_INTERLEAVE_NONE, CU_TENSOR_MAP_SWIZZLE_NONE,
        CU_TENSOR_MAP_L2_PROMOTION_NONE, CU_TENSOR_MAP_FLOAT_OOB_FILL_NONE);
    box[1] = 64;
    enc(&tmo, CU_TENSOR_MAP_DATA_TYPE_BFLOAT16, 2, d_out, gd, gs, box, es, CU_TENSOR_MAP_INTERLEAVE_NONE, CU_TENSOR_MAP_SWIZZLE_NONE,
        CU_TENSOR_MAP_L2_PROMOTION_NONE, CU_TENSOR_MAP_FLOAT_OOB_FILL_NONE);
  }
  Params P;
  P.u = (const uint4*)d_in[0];
  for (int b = 0; b < 2; b++) {
    P.logA[b] = (const uint32_t*)d_in[1 + 7 * b];
    P.Aim[b] = (const uint32_t*)d_in[2 + 7 * b];
    P.Cre[b] = (const uint32_t*)d_in[3 + 7 * b];
    P.Cim[b] = (const uint32_t*)d_in[4 + 7 * b];
    P.logdt[b] = (const uint16_t*)d_in[5 + 7 * b];
    P.Dsk[b] = (const uint16_t*)d_in[6 + 7 * b];
  }
  P.gw = (const uint4*)d_in[14];
  P.out = (uint4*)d_out;
  P.gate = gate_ptr; P.epoch = epoch_ptr;
  s4d_kernel<<<128, 512, SMEM_BYTES>>>(P, tm, tmo);
}
```

```cpp
#include <cuda_runtime.h>
#include <cuda.h>
#include <cuda_bf16.h>
#include <cuda_fp16.h>
#include <stdint.h>

namespace {

constexpr int U1_PLANE = 1184;
constexpr int U1_CH    = 4 * U1_PLANE + 16;
constexpr int OFF_RAW  = 0;
constexpr int OFF_MISC = 32768;
constexpr int OFF_U1   = OFF_MISC + 384;
constexpr int T_D = 0, T_P3 = 1188, T_P5 = 1448, T_P7 = 1708, T_P9 = 1916, CP = 2112, T_BR = 2 * CP;
constexpr int OFF_T    = OFF_U1 + 4 * U1_CH + 64;
constexpr int R_WARP   = 66 * 128;
constexpr int W_WG     = 4 * R_WARP;
constexpr int OFF_W    = OFF_T + 8 * T_BR;
constexpr int V3_OFF = 0, V5_OFF = 3584, V7_OFF = 7168, V9_OFF = 9472, V2_OFF = 11840, V16_P = 576, V9_P = 592;
constexpr int Y_PLANE  = 160, Y_BLK = 8 * Y_PLANE, Y_OWN = 4 * Y_BLK, Y_OFF = 15360, F_OFF = Y_OFF + 2 * Y_OWN - Y_BLK, F_OWN = 3 * Y_BLK;
constexpr int OFF_FIN  = OFF_W + 4 * W_WG;
constexpr int SMEM_BYTES = OFF_FIN + 4 * 2 * Y_BLK;
static_assert(OFF_T % 128 == 0 && OFF_W % 128 == 0 && W_WG % 128 == 0 && F_OFF + Y_BLK + 2 * F_OWN <= W_WG && 4 * Y_OWN + 4 * Y_BLK <= 32768 && SMEM_BYTES <= 232448, "smem");

__device__ unsigned g_epoch;
__device__ unsigned g_gate[2048];

struct Params {
  const uint4* u;
  const uint32_t* logA[2];
  const uint32_t* Aim[2];
  const uint32_t* Cre[2];
  const uint32_t* Cim[2];
  const uint16_t* logdt[2];
  const uint16_t* Dsk[2];
  const uint4* gw;
  uint4* out;
  unsigned* gate;
  unsigned* epoch;
};

template<int N, int TB> __device__ __forceinline__ void wgmma_rs(float* d, uint32_t a0, uint32_t a1, uint32_t a2, uint32_t a3, uint64_t desc);
template<int N, int TB> __device__ __forceinline__ void wgmma_rs_first(float* d, uint32_t a0, uint32_t a1, uint32_t a2, uint32_t a3, uint64_t desc);
template<> __device__ __forceinline__ void wgmma_rs<64,0>(float* d, uint32_t a0, uint32_t a1, uint32_t a2, uint32_t a3, uint64_t desc) {
  asm volatile("wgmma.mma_async.sync.aligned.m64n64k16.f32.bf16.bf16 {%0,%1,%2,%3,%4,%5,%6,%7,%8,%9,%10,%11,%12,%13,%14,%15,%16,%17,%18,%19,%20,%21,%22,%23,%24,%25,%26,%27,%28,%29,%30,%31}, {%32,%33,%34,%35}, %36, 1, 1, 1, 0;"
    : "+f"(d[0]), "+f"(d[1]), "+f"(d[2]), "+f"(d[3]), "+f"(d[4]), "+f"(d[5]), "+f"(d[6]), "+f"(d[7]), "+f"(d[8]), "+f"(d[9]), "+f"(d[10]), "+f"(d[11]), "+f"(d[12]), "+f"(d[13]), "+f"(d[14]), "+f"(d[15]), "+f"(d[16]), "+f"(d[17]), "+f"(d[18]), "+f"(d[19]), "+f"(d[20]), "+f"(d[21]), "+f"(d[22]), "+f"(d[23]), "+f"(d[24]), "+f"(d[25]), "+f"(d[26]), "+f"(d[27]), "+f"(d[28]), "+f"(d[29]), "+f"(d[30]), "+f"(d[31])
    : "r"(a0), "r"(a1), "r"(a2), "r"(a3), "l"(desc));
}
template<> __device__ __forceinline__ void wgmma_rs<56,0>(float* d, uint32_t a0, uint32_t a1, uint32_t a2, uint32_t a3, uint64_t desc) {
  asm volatile("wgmma.mma_async.sync.aligned.m64n56k16.f32.bf16.bf16 {%0,%1,%2,%3,%4,%5,%6,%7,%8,%9,%10,%11,%12,%13,%14,%15,%16,%17,%18,%19,%20,%21,%22,%23,%24,%25,%26,%27}, {%28,%29,%30,%31}, %32, 1, 1, 1, 0;"
    : "+f"(d[0]), "+f"(d[1]), "+f"(d[2]), "+f"(d[3]), "+f"(d[4]), "+f"(d[5]), "+f"(d[6]), "+f"(d[7]), "+f"(d[8]), "+f"(d[9]), "+f"(d[10]), "+f"(d[11]), "+f"(d[12]), "+f"(d[13]), "+f"(d[14]), "+f"(d[15]), "+f"(d[16]), "+f"(d[17]), "+f"(d[18]), "+f"(d[19]), "+f"(d[20]), "+f"(d[21]), "+f"(d[22]), "+f"(d[23]), "+f"(d[24]), "+f"(d[25]), "+f"(d[26]), "+f"(d[27])
    : "r"(a0), "r"(a1), "r"(a2), "r"(a3), "l"(desc));
}
template<> __device__ __forceinline__ void wgmma_rs<48,1>(float* d, uint32_t a0, uint32_t a1, uint32_t a2, uint32_t a3, uint64_t desc) {
  asm volatile("wgmma.mma_async.sync.aligned.m64n48k16.f32.bf16.bf16 {%0,%1,%2,%3,%4,%5,%6,%7,%8,%9,%10,%11,%12,%13,%14,%15,%16,%17,%18,%19,%20,%21,%22,%23}, {%24,%25,%26,%27}, %28, 1, 1, 1, 1;"
    : "+f"(d[0]), "+f"(d[1]), "+f"(d[2]), "+f"(d[3]), "+f"(d[4]), "+f"(d[5]), "+f"(d[6]), "+f"(d[7]), "+f"(d[8]), "+f"(d[9]), "+f"(d[10]), "+f"(d[11]), "+f"(d[12]), "+f"(d[13]), "+f"(d[14]), "+f"(d[15]), "+f"(d[16]), "+f"(d[17]), "+f"(d[18]), "+f"(d[19]), "+f"(d[20]), "+f"(d[21]), "+f"(d[22]), "+f"(d[23])
    : "r"(a0), "r"(a1), "r"(a2), "r"(a3), "l"(desc));
}
template<> __device__ __forceinline__ void wgmma_rs<32,1>(float* d, uint32_t a0, uint32_t a1, uint32_t a2, uint32_t a3, uint64_t desc) {
  asm volatile("wgmma.mma_async.sync.aligned.m64n32k16.f32.bf16.bf16 {%0,%1,%2,%3,%4,%5,%6,%7,%8,%9,%10,%11,%12,%13,%14,%15}, {%16,%17,%18,%19}, %20, 1, 1, 1, 1;"
    : "+f"(d[0]), "+f"(d[1]), "+f"(d[2]), "+f"(d[3]), "+f"(d[4]), "+f"(d[5]), "+f"(d[6]), "+f"(d[7]), "+f"(d[8]), "+f"(d[9]), "+f"(d[10]), "+f"(d[11]), "+f"(d[12]), "+f"(d[13]), "+f"(d[14]), "+f"(d[15])
    : "r"(a0), "r"(a1), "r"(a2), "r"(a3), "l"(desc));
}
template<> __device__ __forceinline__ void wgmma_rs<16,1>(float* d, uint32_t a0, uint32_t a1, uint32_t a2, uint32_t a3, uint64_t desc) {
  asm volatile("wgmma.mma_async.sync.aligned.m64n16k16.f32.bf16.bf16 {%0,%1,%2,%3,%4,%5,%6,%7}, {%8,%9,%10,%11}, %12, 1, 1, 1, 1;"
    : "+f"(d[0]), "+f"(d[1]), "+f"(d[2]), "+f"(d[3]), "+f"(d[4]), "+f"(d[5]), "+f"(d[6]), "+f"(d[7])
    : "r"(a0), "r"(a1), "r"(a2), "r"(a3), "l"(desc));
}
template<> __device__ __forceinline__ void wgmma_rs_first<64,0>(float* d, uint32_t a0, uint32_t a1, uint32_t a2, uint32_t a3, uint64_t desc) {
  asm volatile("wgmma.mma_async.sync.aligned.m64n64k16.f32.bf16.bf16 {%0,%1,%2,%3,%4,%5,%6,%7,%8,%9,%10,%11,%12,%13,%14,%15,%16,%17,%18,%19,%20,%21,%22,%23,%24,%25,%26,%27,%28,%29,%30,%31}, {%32,%33,%34,%35}, %36, 0, 1, 1, 0;"
    : "=f"(d[0]), "=f"(d[1]), "=f"(d[2]), "=f"(d[3]), "=f"(d[4]), "=f"(d[5]), "=f"(d[6]), "=f"(d[7]), "=f"(d[8]), "=f"(d[9]), "=f"(d[10]), "=f"(d[11]), "=f"(d[12]), "=f"(d[13]), "=f"(d[14]), "=f"(d[15]), "=f"(d[16]), "=f"(d[17]), "=f"(d[18]), "=f"(d[19]), "=f"(d[20]), "=f"(d[21]), "=f"(d[22]), "=f"(d[23]), "=f"(d[24]), "=f"(d[25]), "=f"(d[26]), "=f"(d[27]), "=f"(d[28]), "=f"(d[29]), "=f"(d[30]), "=f"(d[31])
    : "r"(a0), "r"(a1), "r"(a2), "r"(a3), "l"(desc));
}
template<> __device__ __forceinline__ void wgmma_rs_first<48,1>(float* d, uint32_t a0, uint32_t a1, uint32_t a2, uint32_t a3, uint64_t desc) {
  asm volatile("wgmma.mma_async.sync.aligned.m64n48k16.f32.bf16.bf16 {%0,%1,%2,%3,%4,%5,%6,%7,%8,%9,%10,%11,%12,%13,%14,%15,%16,%17,%18,%19,%20,%21,%22,%23}, {%24,%25,%26,%27}, %28, 0, 1, 1, 1;"
    : "=f"(d[0]), "=f"(d[1]), "=f"(d[2]), "=f"(d[3]), "=f"(d[4]), "=f"(d[5]), "=f"(d[6]), "=f"(d[7]), "=f"(d[8]), "=f"(d[9]), "=f"(d[10]), "=f"(d[11]), "=f"(d[12]), "=f"(d[13]), "=f"(d[14]), "=f"(d[15]), "=f"(d[16]), "=f"(d[17]), "=f"(d[18]), "=f"(d[19]), "=f"(d[20]), "=f"(d[21]), "=f"(d[22]), "=f"(d[23])
    : "r"(a0), "r"(a1), "r"(a2), "r"(a3), "l"(desc));
}
template<> __device__ __forceinline__ void wgmma_rs_first<32,1>(float* d, uint32_t a0, uint32_t a1, uint32_t a2, uint32_t a3, uint64_t desc) {
  asm volatile("wgmma.mma_async.sync.aligned.m64n32k16.f32.bf16.bf16 {%0,%1,%2,%3,%4,%5,%6,%7,%8,%9,%10,%11,%12,%13,%14,%15}, {%16,%17,%18,%19}, %20, 0, 1, 1, 1;"
    : "=f"(d[0]), "=f"(d[1]), "=f"(d[2]), "=f"(d[3]), "=f"(d[4]), "=f"(d[5]), "=f"(d[6]), "=f"(d[7]), "=f"(d[8]), "=f"(d[9]), "=f"(d[10]), "=f"(d[11]), "=f"(d[12]), "=f"(d[13]), "=f"(d[14]), "=f"(d[15])
    : "r"(a0), "r"(a1), "r"(a2), "r"(a3), "l"(desc));
}
template<> __device__ __forceinline__ void wgmma_rs_first<16,1>(float* d, uint32_t a0, uint32_t a1, uint32_t a2, uint32_t a3, uint64_t desc) {
  asm volatile("wgmma.mma_async.sync.aligned.m64n16k16.f32.bf16.bf16 {%0,%1,%2,%3,%4,%5,%6,%7}, {%8,%9,%10,%11}, %12, 0, 1, 1, 1;"
    : "=f"(d[0]), "=f"(d[1]), "=f"(d[2]), "=f"(d[3]), "=f"(d[4]), "=f"(d[5]), "=f"(d[6]), "=f"(d[7])
    : "r"(a0), "r"(a1), "r"(a2), "r"(a3), "l"(desc));
}

__device__ __forceinline__ void wg_fence()  { asm volatile("wgmma.fence.sync.aligned;" ::: "memory"); }
template<int N> __device__ __forceinline__ void wg_wait() { asm volatile("wgmma.wait_group.sync.aligned %0;" :: "n"(N) : "memory"); }
template<int N> __device__ __forceinline__ void fence_regs(float* d) {
  #pragma unroll
  for (int i = 0; i < N; i++) asm volatile("" : "+f"(d[i]) :: "memory");
}
template<int N> __device__ __forceinline__ void redef(float* d) {
  #pragma unroll
  for (int i = 0; i < N; i++) { float y; asm volatile("mov.b32 %0, %1;" : "=f"(y) : "f"(d[i])); d[i] = y; }
}
__device__ __forceinline__ uint64_t mkdesc(uint32_t addr, uint32_t lbo, uint32_t sbo) {
  return (uint64_t)((addr & 0x3FFFF) >> 4) | ((uint64_t)(lbo >> 4) << 16) | ((uint64_t)(sbo >> 4) << 32);
}
__device__ __forceinline__ void bar_sync(int id, int n) { asm volatile("bar.sync %0, %1;" :: "r"(id), "r"(n) : "memory"); }
__device__ __forceinline__ uint32_t lds32(uint32_t a) { uint32_t v; asm volatile("ld.shared.u32 %0, [%1];" : "=r"(v) : "r"(a)); return v; }
__device__ __forceinline__ uint4 lds128(uint32_t a) { uint4 v; asm volatile("ld.shared.v4.u32 {%0,%1,%2,%3}, [%4];" : "=r"(v.x), "=r"(v.y), "=r"(v.z), "=r"(v.w) : "r"(a)); return v; }
__device__ __forceinline__ uint4 lds128p(bool p, uint32_t a) {
  uint4 v = make_uint4(0, 0, 0, 0);
  asm volatile("{.reg .pred p; setp.ne.u32 p, %5, 0; @p ld.shared.v4.u32 {%0,%1,%2,%3}, [%4];}" : "+r"(v.x), "+r"(v.y), "+r"(v.z), "+r"(v.w) : "r"(a), "r"((uint32_t)p));
  return v;
}
__device__ __forceinline__ uint32_t lds32p(bool p, uint32_t a) {
  uint32_t v;
  asm volatile("{.reg .pred p; setp.ne.u32 p, %2, 0; mov.b32 %0, 0; @p ld.shared.u32 %0, [%1];}" : "=r"(v) : "r"(a), "r"((uint32_t)p));
  return v;
}
__device__ __forceinline__ void ldsm4t(uint32_t& r0, uint32_t& r1, uint32_t& r2, uint32_t& r3, uint32_t a) {
  asm volatile("ldmatrix.sync.aligned.m8n8.x4.trans.shared.b16 {%0,%1,%2,%3}, [%4];" : "=r"(r0), "=r"(r1), "=r"(r2), "=r"(r3) : "r"(a) : "memory");
}
__device__ __forceinline__ void ldsm4(uint32_t& r0, uint32_t& r1, uint32_t& r2, uint32_t& r3, uint32_t a) {
  asm volatile("ldmatrix.sync.aligned.m8n8.x4.shared.b16 {%0,%1,%2,%3}, [%4];" : "=r"(r0), "=r"(r1), "=r"(r2), "=r"(r3) : "r"(a) : "memory");
}
__device__ __forceinline__ void stsm4(uint32_t a, uint32_t r0, uint32_t r1, uint32_t r2, uint32_t r3) {
  asm volatile("stmatrix.sync.aligned.m8n8.x4.shared.b16 [%0], {%1,%2,%3,%4};" :: "r"(a), "r"(r0), "r"(r1), "r"(r2), "r"(r3) : "memory");
}
__device__ __forceinline__ void stsm4t(uint32_t a, uint32_t r0, uint32_t r1, uint32_t r2, uint32_t r3) {
  asm volatile("stmatrix.sync.aligned.m8n8.x4.trans.shared.b16 [%0], {%1,%2,%3,%4};" :: "r"(a), "r"(r0), "r"(r1), "r"(r2), "r"(r3) : "memory");
}
__device__ __forceinline__ void sts16(uint32_t a, uint32_t v) { asm volatile("st.shared.u16 [%0], %1;" :: "r"(a), "r"(v) : "memory"); }
__device__ __forceinline__ void sts32(uint32_t a, uint32_t v) { asm volatile("st.shared.u32 [%0], %1;" :: "r"(a), "r"(v) : "memory"); }
__device__ __forceinline__ void sts128(uint32_t a, uint32_t x, uint32_t y, uint32_t z, uint32_t w) { asm volatile("st.shared.v4.u32 [%0], {%1,%2,%3,%4};" :: "r"(a), "r"(x), "r"(y), "r"(z), "r"(w) : "memory"); }
__device__ __forceinline__ uint32_t mapa(uint32_t a, uint32_t r) { uint32_t v; asm("mapa.shared::cluster.u32 %0, %1, %2;" : "=r"(v) : "r"(a), "r"(r)); return v; }
__device__ __forceinline__ float ex2(float x) { float y; asm("ex2.approx.ftz.f32 %0, %1;" : "=f"(y) : "f"(x)); return y; }
__device__ __forceinline__ float fsin(float x) { float y; asm("sin.approx.ftz.f32 %0, %1;" : "=f"(y) : "f"(x)); return y; }
__device__ __forceinline__ float fcos(float x) { float y; asm("cos.approx.ftz.f32 %0, %1;" : "=f"(y) : "f"(x)); return y; }
__device__ __forceinline__ float bf_lo(uint32_t w) { return __uint_as_float(w << 16); }
__device__ __forceinline__ float bf_hi(uint32_t w) { return __uint_as_float(w & 0xFFFF0000u); }
__device__ __forceinline__ uint32_t pk_h(float lo, float hi) { uint32_t d; asm("cvt.rn.f16x2.f32 %0, %1, %2;" : "=r"(d) : "f"(hi), "f"(lo)); return d; }
__device__ __forceinline__ uint32_t pk_bf(float lo, float hi) { uint32_t d; asm("cvt.rn.bf16x2.f32 %0, %1, %2;" : "=r"(d) : "f"(hi), "f"(lo)); return d; }
__device__ __forceinline__ uint32_t badd(uint32_t a, uint32_t b) { uint32_t d; asm("add.rn.bf16x2 %0, %1, %2;" : "=r"(d) : "r"(a), "r"(b)); return d; }
__device__ __forceinline__ uint32_t bmul(uint32_t a, uint32_t b) { uint32_t d; asm("mul.rn.bf16x2 %0, %1, %2;" : "=r"(d) : "r"(a), "r"(b)); return d; }
__device__ __forceinline__ uint32_t bsub(uint32_t a, uint32_t b) { uint32_t d; asm("sub.rn.bf16x2 %0, %1, %2;" : "=r"(d) : "r"(a), "r"(b)); return d; }
struct C2 { uint32_t r, i; };
__device__ __forceinline__ uint32_t hmul(uint32_t a, uint32_t b) { uint32_t d; asm("mul.rn.f16x2 %0, %1, %2;" : "=r"(d) : "r"(a), "r"(b)); return d; }
__device__ __forceinline__ uint32_t hfma(uint32_t a, uint32_t b, uint32_t c) { uint32_t d; asm("fma.rn.f16x2 %0, %1, %2, %3;" : "=r"(d) : "r"(a), "r"(b), "r"(c)); return d; }
__device__ __forceinline__ uint32_t hfnma(uint32_t a, uint32_t b, uint32_t c) {
  uint32_t d; asm("{.reg .b32 t; neg.f16x2 t, %1; fma.rn.f16x2 %0, t, %2, %3;}" : "=r"(d) : "r"(a), "r"(b), "r"(c)); return d;
}
__device__ __forceinline__ C2 cmul(C2 x, C2 z)  { C2 o; o.r = hfnma(x.i, z.i, hmul(x.r, z.r)); o.i = hfma(x.i, z.r, hmul(x.r, z.i)); return o; }
__device__ __forceinline__ C2 cmulc(C2 x, C2 z) { C2 o; o.r = hfma(x.i, z.i, hmul(x.r, z.r)); o.i = hfnma(x.r, z.i, hmul(x.i, z.r)); return o; }
__device__ __forceinline__ void csq(float& r, float& i) { float t = i * i; float n = fmaf(r, r, -t); i = __uint_as_float(__float_as_uint(r * i) + 0x00800000u); r = n; }

__device__ __forceinline__ uint32_t cpy(uint32_t x) { uint32_t y; asm volatile("mov.b32 %0, %1;" : "=r"(y) : "r"(x)); return y; }
__device__ __forceinline__ void keep(uint32_t& x) { asm volatile("" : "+r"(x)); }
__device__ __forceinline__ int tid_now() { int t; asm volatile("mov.u32 %0, %%tid.x;" : "=r"(t)); return t; }
struct Frag { uint32_t a0, a1, a2, a3; };
template<int TOP> __device__ __forceinline__ uint32_t tap_word(uint32_t base, int p, int hh) {
  if (p <= -3 || 8 * p - 7 > TOP) return cpy(0u);
  if (p <= -1) return lds32p(hh, base - 16 * p);
  if (8 * p + 9 > TOP) return lds32p(!hh, base - 16 * p);
  return lds32(base - 16 * p);
}
template<int N, int TOP = 63> __device__ __forceinline__ void raw_load(uint32_t* raw, uint32_t base, int p, int hh) {
  #pragma unroll
  for (int i = 0; i < N; i++) raw[i] = tap_word<TOP>(base, p - 1 + i, hh);
}
__device__ __forceinline__ Frag mkfrag(const uint32_t* r, bool first) { Frag f; f.a0 = r[1]; f.a1 = r[2]; f.a2 = first ? r[0] : cpy(r[0]); f.a3 = cpy(r[1]); return f; }
template<int S> __device__ __forceinline__ void dense_step(float* acc, const Frag& f, uint64_t d0) {
  constexpr int kk = S & 1, m = (S + 1) >> 1;
  constexpr int N = (m < 8) ? 64 : 56;
  if constexpr (S == -1) wgmma_rs_first<64, 0>(acc, f.a0, f.a1, f.a2, f.a3, d0 + (uint64_t)((2 * kk * U1_PLANE + m * 16) >> 4));
  else wgmma_rs<N, 0>(acc, f.a0, f.a1, f.a2, f.a3, d0 + (uint64_t)((2 * kk * U1_PLANE + m * 16) >> 4));
}
template<int S0, int NS> __device__ __forceinline__ void dense_load(uint32_t* raw, uint32_t base, int hh) {
  #pragma unroll
  for (int i = 1; i <= 2 * NS; i++) raw[i] = tap_word<514>(base, 2 * S0 - 1 + i, hh);
}
template<int S0, int NS, int W> __device__ __forceinline__ void dense_group(float* acc, uint32_t* raw, uint64_t d0) {
  Frag f[3];
  #pragma unroll
  for (int i = 0; i < NS; i++) f[i] = mkfrag(raw + 2 * i, i == 0);
  raw[0] = cpy(raw[2 * NS]);
  wg_fence();
  dense_step<S0>(acc, f[0], d0); dense_step<S0 + 1>(acc, f[1], d0);
  if constexpr (NS > 2) dense_step<S0 + 2>(acc, f[2], d0);
  asm volatile("wgmma.commit_group.sync.aligned;" ::: "memory");
  wg_wait<W>();
}
template<int S, int N, bool FIRST = false, int BS = 512> __device__ __forceinline__ void far_step(float* acc, const Frag& f, uint64_t d0) {
  constexpr int fl = (S >= 0) ? (S / 2) : -((1 - S) / 2);
  if constexpr (FIRST) wgmma_rs_first<N, 1>(acc, f.a0, f.a1, f.a2, f.a3, d0 + (uint64_t)(((-fl) * BS + (S & 1) * 256) >> 4));
  else wgmma_rs<N, 1>(acc, f.a0, f.a1, f.a2, f.a3, d0 + (uint64_t)(((-fl) * BS + (S & 1) * 256) >> 4));
}
template<int S, int N, bool FIRST = false, int BS = 512, int BS2 = BS> __device__ __forceinline__ void far_group(float* acc, const uint32_t* raw, uint64_t da, uint64_t db) {
  const Frag f0 = mkfrag(raw, true), f1 = mkfrag(raw + 2, false), f2 = mkfrag(raw + 5, true), f3 = mkfrag(raw + 7, false);
  wg_fence();
  far_step<S, N, FIRST, BS>(acc, f0, da); far_step<S - 1, N, false, BS>(acc, f1, da); far_step<S, N, false, BS2>(acc, f2, db); far_step<S - 1, N, false, BS2>(acc, f3, db);
  asm volatile("wgmma.commit_group.sync.aligned;" ::: "memory");
}
__device__ __forceinline__ void mma16816bf(float* c, uint32_t a0, uint32_t a1, uint32_t a2, uint32_t a3, uint32_t b0, uint32_t b1) {
  asm volatile("mma.sync.aligned.m16n8k16.row.col.f32.bf16.bf16.f32 {%0,%1,%2,%3}, {%4,%5,%6,%7}, {%8,%9}, {%0,%1,%2,%3};"
    : "+f"(c[0]), "+f"(c[1]), "+f"(c[2]), "+f"(c[3]) : "r"(a0), "r"(a1), "r"(a2), "r"(a3), "r"(b0), "r"(b1));
}
__device__ __forceinline__ void mbar_wait(uint32_t bar, uint32_t parity) {
  uint32_t ok = 0; int it = 0;
  do {
    asm volatile("{.reg .pred p; mbarrier.try_wait.parity.shared::cta.b64 p, [%1], %2, 20000; selp.u32 %0, 1, 0, p;}" : "=r"(ok) : "r"(bar), "r"(parity) : "memory");
  } while (!ok && ++it < (1 << 16));
}
__device__ __forceinline__ void cexp2(float& r, float& i, float e, float x) {
  const float k = __fadd_rn(fmaf(x, 0.15915494309189535f, 12582912.f), -12582912.f);
  const float m = ex2(e), a = fmaf(k, -6.283185307179586f, x);
  r = m * fcos(a); i = m * fsin(a);
}
__device__ __forceinline__ void mma16816h(uint32_t* c, uint32_t a0, uint32_t a1, uint32_t a2, uint32_t a3, uint32_t b0, uint32_t b1) {
  asm("mma.sync.aligned.m16n8k16.row.col.f16.f16.f16.f16 {%0,%1}, {%2,%3,%4,%5}, {%6,%7}, {%0,%1};"
    : "+r"(c[0]), "+r"(c[1]) : "r"(a0), "r"(a1), "r"(a2), "r"(a3), "r"(b0), "r"(b1));
}
__device__ __forceinline__ float h_lo(uint32_t w) { return __half2float(__ushort_as_half((unsigned short)(w & 0xFFFFu))); }
__device__ __forceinline__ float h_hi(uint32_t w) { return __half2float(__ushort_as_half((unsigned short)(w >> 16))); }

__device__ __forceinline__ void load_E(uint32_t* E, uint32_t a0, uint32_t a1, uint32_t a2) {
  const uint4 e0 = lds128(a0), e1 = lds128(a1), e2 = lds128(a2);
  E[0] = e0.x; E[1] = e0.y; E[2] = e0.z; E[3] = e0.w; E[4] = e1.x; E[5] = e1.y; E[6] = e1.z; E[7] = e1.w; E[8] = e2.x; E[9] = e2.y; E[10] = e2.z; E[11] = e2.w;
}
template<bool FULL> __device__ __forceinline__ void build_V(const uint32_t* E, uint32_t o8, uint32_t o16, uint32_t o9) {
  uint32_t O[11], Q[11], R[10], V3[11], V5[10];
  #pragma unroll
  for (int n = FULL ? 3 : 4; n <= 10; n++) { O[n] = __byte_perm(E[n - 1], E[n], 0x5432); Q[n] = badd(O[n], E[n - 1]); }
  #pragma unroll
  for (int n = FULL ? 4 : 5; n <= (FULL ? 9 : 8); n++) R[n] = badd(Q[n], Q[n - 1]);
  #pragma unroll
  for (int n = FULL ? 4 : 7; n <= 10; n++) V3[n] = badd(Q[n], O[n - 1]);
  #pragma unroll
  for (int n = 5; n <= (FULL ? 9 : 8); n++) V5[n] = badd(E[n], R[n]);
  sts128(o8 + V3_OFF, V3[7], V3[8], V3[9], V3[10]);
  sts128(o8 + V5_OFF, V5[5], V5[6], V5[7], V5[8]);
  if (FULL) {
    sts128(o16 + V7_OFF, badd(R[6], V3[4]), badd(R[7], V3[5]), badd(R[8], V3[6]), badd(R[9], V3[7]));
    sts128(o9, badd(V5[6], R[4]), badd(V5[7], R[5]), badd(V5[8], R[6]), badd(V5[9], R[7]));
    sts128(o16 + V2_OFF, Q[7], Q[8], Q[9], Q[10]);
  }
}

__global__ void __cluster_dims__(2, 1, 1) __launch_bounds__(512, 1)
s4d_kernel(const __grid_constant__ Params P, const __grid_constant__ CUtensorMap tmU, const __grid_constant__ CUtensorMap tmO) {
  extern __shared__ __align__(256) uint8_t smem[];
  const int tid = threadIdx.x, lane = tid & 31, wi = __shfl_sync(0xFFFFFFFFu, tid >> 5, 0), wg = wi >> 2, wq = wi & 3;
  const int br = wq >> 1, hh = wq & 1;
  const unsigned pch = blockIdx.x * 4 + wg, pw = pch * 64 + hh * 32;
  const uint32_t wLA = __ldg(P.logA[br] + pw + lane), wAI = __ldg(P.Aim[br] + pw + lane);
  const uint32_t wDT = __ldg(P.logdt[br] + pch);
  const uint32_t wCR = __ldg(P.Cre[br] + pw + lane), wCI = __ldg(P.Cim[br] + pw + lane);
  const uint32_t wCR2 = __ldg(P.Cre[br] + (pw ^ 32) + lane), wCI2 = __ldg(P.Cim[br] + (pw ^ 32) + lane);
  const uint32_t wDS = __ldg(P.Dsk[br] + pch);
  unsigned epoch;
  asm volatile("ld.relaxed.gpu.global.u32 %0, [%1];" : "=r"(epoch) : "l"(P.epoch) : "memory");
  const uint32_t sb = (uint32_t)__cvta_generic_to_shared(smem);
  const int g = lane >> 2, q = lane & 3;
  const int rank = blockIdx.x & 1, clus = blockIdx.x >> 1;
  const uint32_t barU = sb + OFF_MISC, barY = sb + OFF_MISC + 8, junk = sb + OFF_MISC + 128;
  const bool gater = wg == 3;

  const uint32_t sT = sb + OFF_T + (wg * 2 + br) * T_BR;
  const uint32_t sU = sb + OFF_U1 + wg * U1_CH;
  const uint32_t sW = sb + OFF_W + wg * W_WG;
  const uint32_t sR = sW + wq * R_WARP;
  const uint32_t l4 = lane * 4, l16 = lane * 16;
  const uint32_t we = sR + l4, wo = sR + (l4 ^ 64);
  #pragma unroll
  for (int k = 0; k < 4; k++) sts128(sT + hh * CP + l16 + k * 512, 0, 0, 0, 0);
  if (lane < 10) {
    sts128(sU + wq * U1_PLANE + 1024 + l16, 0, 0, 0, 0);
    if (lane < 4) sts128(sT + hh * CP + 2048 + l16, 0, 0, 0, 0);
  }
  sts32(we + 48 * 128, 0x3C003C00u); sts32(we + 56 * 128, 0u);
  const bool lo = q < 2, fix = (hh == 0) && !(lane & 29);
  const uint32_t jk = sR + 2560, q64 = (lane & 1) * 64;
  const uint32_t c0 = sT + T_D + 606 - 256 * hh - l4 - 4 * q, p3 = sT + T_P3 + 190 - 32 * hh - 2 * g - q64;
  uint32_t tb0 = sT + T_D + 1116 - 256 * hh - l4;
  uint32_t tcl = lo ? c0 : jk + ((c0 + 12) & 127u);
  const uint32_t pa = sT + ((lane & 4) ? T_P7 + 126 : T_P9 + 128) - 16 * hh - (g & 6) - q64;
  uint32_t tpa = lo ? pa : jk + ((pa + 32) & 127u);
  uint32_t tu2 = lo ? c0 - 4 : p3, tu4 = tu2 - (lo ? 128 : 16);
  uint32_t tu1 = tu2 + (lo ? 6 : (T_P5 - T_P3) + 2);
  uint32_t tm1 = lo ? pa - 32 : p3 + (T_P5 - T_P3) + CP + 4, tm2 = lo ? pa - 32 + CP + 2 : p3 + CP + 2;
  uint32_t tm3 = tm1 - (lo ? 8 : 16);
  uint32_t tcf = tcl, tcg = tcl, tpaf = tpa;
  if (fix) {
    tu1 = sT + (lo ? T_D + CP + 2 * (560 - 256) : T_D + 96);
    tpaf = sT + (lo ? T_P5 + 64 : T_P9);
    tcf = lo ? jk + 2 : sT + T_D + 94;
    if (!lo) { tm1 = sT + T_D + 90; tcg = sT + T_D + 94; }
  }
  const int rw = (lane & 7) - 4 * rank;
  uint32_t xdst = sb + OFF_U1 + (63 - 8 * ((wi - 4) & 7)) * 16 + (lane >> 3) * U1_PLANE + rw * U1_CH;
  if ((unsigned)rw >= 4u) xdst = junk + 128 + (xdst & 127u);
  const uint32_t xsrc = sb + OFF_RAW + ((wi - 4) & 7) * 4096 + l16;
  uint32_t gL = sT - 32 * hh + ((lane & 4) ? 0 : CP + 2) - 2 * g + 4 * q;
  const int role = (wq + wg) & 3;
  uint32_t ve2 = sU + (63 - 8 * role) * 16 + q * U1_PLANE - g * 16;
  uint32_t ve1 = ve2 + (q == 0 ? 3 * U1_PLANE + 16 : -U1_PLANE), ve0 = ve2 + (lo ? 2 * U1_PLANE + 16 : -2 * U1_PLANE);
  const uint32_t vo8 = sW + (5 - role) * 512 + l16;
  uint32_t vo16 = sW + (1 - (role >> 1)) * 2 * V16_P + (role & 1) * 256 + q64 * (V16_P / 64) + (lane >> 1) * 16;
  uint32_t vo9 = vo16 + V9_OFF + (1 - (role >> 1)) * 2 * (V9_P - V16_P) + ((lane & 1) ? 16 - V16_P : V9_P);
  if (lane == 31 && (role & 1)) vo9 = (role == 3) ? junk : sW + V9_OFF;
  keep(ve0); keep(ve1); keep(ve2); keep(vo16); keep(vo9);
  keep(tb0); keep(tcl); keep(tpa); keep(tu1); keep(tu2); keep(tu4); keep(tcf); keep(tcg); keep(tpaf); keep(tm1); keep(tm2); keep(tm3); keep(xdst); keep(gL);

  asm volatile("fence.proxy.async.shared::cta;" ::: "memory");
  __syncwarp();
  if (lane == 0 && gater) {
    asm volatile("cp.async.bulk.global.shared::cta.bulk_group [%0], [%1], 2048;" :: "l"(P.out + (size_t)(blockIdx.x * 16 + wq * 4) * 64), "r"(sT + hh * CP) : "memory");
    asm volatile("cp.async.bulk.global.shared::cta.bulk_group [%0], [%1], 2048;" :: "l"(P.out + (size_t)(blockIdx.x * 16 + wq * 4 + 2) * 64), "r"(sT + hh * CP) : "memory");
    asm volatile("cp.async.bulk.commit_group;" ::: "memory");
  }
  if (tid == 480) {
    asm volatile("prefetch.tensormap [%0];" :: "l"(&tmU) : "memory");
    asm volatile("prefetch.tensormap [%0];" :: "l"(&tmO) : "memory");
    asm volatile("mbarrier.init.shared::cta.b64 [%0], 1;" :: "r"(barU) : "memory");
    asm volatile("mbarrier.init.shared::cta.b64 [%0], 8;" :: "r"(barU + 40) : "memory");
    asm volatile("mbarrier.init.shared::cta.b64 [%0], 17;" :: "r"(barY + 24) : "memory");
    asm volatile("mbarrier.init.shared::cta.b64 [%0], 17;" :: "r"(barY + 40) : "memory");
    asm volatile("mbarrier.arrive.expect_tx.shared::cta.b64 _, [%0], %1;" :: "r"(barY + 40), "r"(4096) : "memory");
    asm volatile("mbarrier.init.shared::cta.b64 [%0], 5;" :: "r"(barY) : "memory");
    asm volatile("mbarrier.init.shared::cta.b64 [%0], 17;" :: "r"(barY + 8) : "memory");
    asm volatile("mbarrier.init.shared::cta.b64 [%0], 17;" :: "r"(barY + 16) : "memory");
    asm volatile("mbarrier.arrive.expect_tx.shared::cta.b64 _, [%0], %1;" :: "r"(barU), "r"(32768) : "memory");
    asm volatile("mbarrier.arrive.expect_tx.shared::cta.b64 _, [%0], %1;" :: "r"(barY), "r"(12 * Y_BLK) : "memory");
    asm volatile("mbarrier.arrive.expect_tx.shared::cta.b64 _, [%0], %1;" :: "r"(barY + 8), "r"(4096) : "memory");
    asm volatile("mbarrier.arrive.expect_tx.shared::cta.b64 _, [%0], %1;" :: "r"(barY + 16), "r"(4096) : "memory");
    asm volatile("mbarrier.arrive.expect_tx.shared::cta.b64 _, [%0], %1;" :: "r"(barY + 24), "r"(4096) : "memory");
    asm volatile("fence.mbarrier_init.release.cluster;" ::: "memory");
  }
  __syncwarp();
  asm volatile("barrier.cluster.arrive.relaxed.aligned;" ::: "memory");
  if (wi == 15) {
    asm volatile("barrier.cluster.wait.aligned;" ::: "memory");
    if (lane == 0) {
      #pragma unroll
      for (int k = 0; k < 4; k++)
        asm volatile("cp.async.bulk.tensor.2d.shared::cluster.global.mbarrier::complete_tx::bytes.multicast::cluster [%0], [%1, {%3, %4}], [%2], %5;"
          :: "r"(sb + OFF_RAW + (rank * 1024 + k * 256) * 16), "l"(&tmU), "r"(barU), "r"(clus * 8), "r"(rank * 1024 + k * 256), "h"((unsigned short)3) : "memory");
    }
    __syncwarp();
  }

  const float dt = bf_lo(pk_bf(ex2(bf_lo(wDT) * 1.4426950408889634f), 0.f));
  float csc, tsc;
  {
    uint32_t m = __vmaxu2(__vmaxu2(wCR & 0x7FFF7FFFu, wCI & 0x7FFF7FFFu), __vmaxu2(wCR2 & 0x7FFF7FFFu, wCI2 & 0x7FFF7FFFu));
    m = max(m & 0xFFFFu, m >> 16);
    m = __reduce_max_sync(0xFFFFFFFFu, m);
    int k = 134 - (int)(m >> 7);
    k = min(max(k, -126), 126);
    csc = __uint_as_float((uint32_t)(k + 127) << 23);
    tsc = 2.0f * dt * __uint_as_float((uint32_t)(127 - k) << 23);
  }
  {
    const uint32_t Ab = pk_bf(ex2(bf_lo(wLA) * 1.4426950408889634f), ex2(bf_hi(wLA) * 1.4426950408889634f));
    const float ndt = dt * -1.4426950408889634f;
    const float ea = bf_lo(Ab) * ndt, eb = bf_hi(Ab) * ndt, ta = bf_lo(wAI) * dt, tb = bf_hi(wAI) * dt;
    float ra, ia, rb, ib;
    cexp2(ra, ia, ea, ta); cexp2(rb, ib, eb, tb);
#define PK1 C2{pk_h(ra, rb), pk_h(ia, ib)}
#define SQ1 csq(ra, ia); csq(rb, ib);
#define PUT(T, G, V) { sts32(((G) & 1 ? wo : we) + ((T) * 16 + (G)) * 128, (V).r); sts32(((G) & 1 ? wo : we) + ((T) * 16 + 8 + (G)) * 128, (V).i); }
    C2 H0[8], X[8], H1[8], H2[5];
    H0[0] = C2{pk_h(bf_lo(wCR) * csc, bf_hi(wCR) * csc), pk_h(bf_lo(wCI) * -csc, bf_hi(wCI) * -csc)}; PUT(0, 0, H0[0])
    const C2 m1 = PK1; H0[1] = cmulc(H0[0], m1); PUT(0, 1, H0[1])
    SQ1 const C2 m2 = PK1;
    H0[2] = cmulc(H0[0], m2); PUT(0, 2, H0[2]) H0[3] = cmulc(H0[1], m2); PUT(0, 3, H0[3])
    SQ1 const C2 m4 = PK1;
    H0[4] = cmulc(H0[0], m4); PUT(0, 4, H0[4]) H0[5] = cmulc(H0[1], m4); PUT(0, 5, H0[5])
    SQ1 X[1] = PK1; PUT(3, 1, X[1])
    H0[6] = cmulc(H0[2], m4); PUT(0, 6, H0[6]) H0[7] = cmulc(H0[3], m4); PUT(0, 7, H0[7])
    SQ1 X[2] = PK1; PUT(3, 2, X[2])
    X[3] = cmul(X[2], X[1]); PUT(3, 3, X[3])
    SQ1 X[4] = PK1; PUT(3, 4, X[4])
    X[5] = cmul(X[4], X[1]); PUT(3, 5, X[5]) X[6] = cmul(X[4], X[2]); PUT(3, 6, X[6])
    SQ1 const C2 Z = PK1;
    sts32(we + 64 * 128, Z.r); sts32(we + 65 * 128, Z.i);
    X[7] = cmul(X[6], X[1]); PUT(3, 7, X[7])
    SQ1 SQ1 const C2 m256 = PK1;
    H1[0] = cmulc(H0[0], m256); PUT(1, 0, H1[0]) H1[1] = cmulc(H0[2], m256); PUT(1, 1, H1[1])
    SQ1 const C2 m512 = PK1;
    H1[2] = cmulc(H0[4], m256); PUT(1, 2, H1[2]) H1[3] = cmulc(H0[6], m256); PUT(1, 3, H1[3])
    SQ1 const C2 m1k = PK1;
    H1[4] = cmulc(H0[0], m512); PUT(1, 4, H1[4]) H1[5] = cmulc(H0[4], m512); PUT(1, 5, H1[5])
    H1[6] = cmulc(H1[0], m512); PUT(1, 6, H1[6]) H1[7] = cmulc(H1[2], m512); PUT(1, 7, H1[7])
    H2[0] = cmulc(H0[0], m1k); PUT(2, 0, H2[0]) H2[1] = cmulc(H1[0], m1k); PUT(2, 1, H2[1])
    H2[2] = cmulc(H1[4], m1k); PUT(2, 2, H2[2]) H2[3] = cmulc(H1[6], m1k); PUT(2, 3, H2[3])
    H2[4] = cmulc(H2[0], m1k); PUT(2, 4, H2[4])
#undef PUT
#undef PK1
#undef SQ1
  }
  if (wi != 15) asm volatile("barrier.cluster.wait.aligned;" ::: "memory");
  __syncwarp();
  uint32_t cD[2][3][2];
  #pragma unroll
  for (int i = 0; i < 12; i++) (&cD[0][0][0])[i] = 0u;
  {
    #pragma unroll
    for (int h2 = 0; h2 < 2; h2++) {
      const uint32_t r0 = sR + g * 128 + 16 * ((q + 4 * h2) ^ (4 * (g & 1))), zb = sR + 64 * 128 + 16 * (q + 4 * h2);
      const uint4 Xr = lds128(r0 + 48 * 128), Xi = lds128(r0 + 56 * 128), Zr = lds128(zb), Zi = lds128(zb + 128);
      const uint4 H0r = lds128(r0), H0i = lds128(r0 + 8 * 128), H1r = lds128(r0 + 16 * 128), H1i = lds128(r0 + 24 * 128);
      const uint4 H2r = lds128p(g < 6, r0 + 32 * 128), H2i = lds128p(g < 6, r0 + 40 * 128);
#define KSTEP(E, F) { \
      const C2 za = C2{Zr.E, Zi.E}, zc = C2{Zr.F, Zi.F}, a0 = C2{Xr.E, Xi.E}, c0 = C2{Xr.F, Xi.F}; \
      const C2 a1 = cmul(a0, za), c1 = cmul(c0, zc), a2 = cmul(a1, za), c2 = cmul(c1, zc), a3 = cmul(a2, za), c3 = cmul(c2, zc); \
      mma16816h(cD[0][0], a0.r, a1.r, c0.r, c1.r, H0r.E, H0r.F); mma16816h(cD[0][1], a0.r, a1.r, c0.r, c1.r, H1r.E, H1r.F); \
      mma16816h(cD[0][2], a0.r, a1.r, c0.r, c1.r, H2r.E, H2r.F); \
      mma16816h(cD[0][0], a0.i, a1.i, c0.i, c1.i, H0i.E, H0i.F); mma16816h(cD[0][1], a0.i, a1.i, c0.i, c1.i, H1i.E, H1i.F); \
      mma16816h(cD[0][2], a0.i, a1.i, c0.i, c1.i, H2i.E, H2i.F); \
      mma16816h(cD[1][0], a2.r, a3.r, c2.r, c3.r, H0r.E, H0r.F); mma16816h(cD[1][1], a2.r, a3.r, c2.r, c3.r, H1r.E, H1r.F); \
      mma16816h(cD[1][2], a2.r, a3.r, c2.r, c3.r, H2r.E, H2r.F); \
      mma16816h(cD[1][0], a2.i, a3.i, c2.i, c3.i, H0i.E, H0i.F); mma16816h(cD[1][1], a2.i, a3.i, c2.i, c3.i, H1i.E, H1i.F); \
      mma16816h(cD[1][2], a2.i, a3.i, c2.i, c3.i, H2i.E, H2i.F); }
      KSTEP(x, y) KSTEP(z, w)
#undef KSTEP
    }
  }
  __syncwarp();
  uint4 gx[8], gw0, gw1;
  if (gater) {
    const size_t grow = (size_t)(blockIdx.x * 16 + wq * 4) * 64 + lane;
    #pragma unroll
    for (int r = 0; r < 8; r++) gx[r] = __ldg(P.u + grow + r * 32);
    gw0 = __ldg(P.gw + lane); gw1 = __ldg(P.gw + 32 + lane);
    if (lane == 0) asm volatile("cp.async.bulk.wait_group 0;" ::: "memory");
    __syncwarp();
  } else if (wg) {
    mbar_wait(barU, 0);
    #pragma unroll
    for (int k = 0; k < 8; k += 4) {
      uint32_t r[4][4];
      #pragma unroll
      for (int j = 0; j < 4; j++) ldsm4t(r[j][0], r[j][1], r[j][2], r[j][3], xsrc + (k + j) * 512);
      #pragma unroll
      for (int j = 0; j < 4; j++) stsm4(xdst - 16 * (k + j), r[j][0], r[j][1], r[j][2], r[j][3]);
    }
    asm volatile("fence.proxy.async.shared::cta;" ::: "memory");
    __syncwarp();
    if (lane == 0) asm volatile("mbarrier.arrive.shared::cta.b64 _, [%0];" :: "r"(barU + 40) : "memory");
  }
  asm volatile("barrier.cluster.arrive.relaxed.aligned;" ::: "memory");
  float v[12];
  {
    const uint32_t sO = sW + (wq ^ 1) * R_WARP + lane * 16, sS = sR + lane * 16;
#define XCH(SND, KEEP) \
    sts128(sS, cD[SND][0][0], cD[SND][0][1], cD[SND][1][0], cD[SND][1][1]); sts32(sR + 512 + l4, cD[SND][2][0]); sts32(sR + 640 + l4, cD[SND][2][1]); \
    bar_sync(1 + wg * 2 + br, 64); \
    { const uint4 o = lds128(sO), p = make_uint4(lds32(sO - l16 + 512 + l4), lds32(sO - l16 + 640 + l4), 0u, 0u); const uint32_t w[6] = {o.x, o.y, o.z, o.w, p.x, p.y}; \
      _Pragma("unroll") for (int k = 0; k < 6; k++) { \
        v[2 * k] = (h_lo(cD[KEEP][k >> 1][k & 1]) + h_lo(w[k])) * tsc; v[2 * k + 1] = (h_hi(cD[KEEP][k >> 1][k & 1]) + h_hi(w[k])) * tsc; } }
    if (hh) { XCH(0, 1) } else { XCH(1, 0) }
#undef XCH
  }
  {
    if (hh == 0 && lane == 0) v[0] += bf_lo(wDS);
    #pragma unroll
    for (int a = 0; a < 2; a++) {
      const uint32_t w0 = pk_bf(v[2 * a + 1], v[2 * a]);
      sts32(tb0 - 128 * a, w0);
      sts16(tb0 - 128 * a + CP + 4, w0 >> 16);
      sts16(tb0 - 128 * a + CP + 2, w0);
      const uint32_t w1 = pk_bf(v[4 + 2 * a], v[5 + 2 * a]);
      const uint32_t aa = __byte_perm(w1, 0, 0x1010), ba = __byte_perm(w1, 0, 0x1032);
      sts16(a ? tu4 + (lo ? 6 : (T_P5 - T_P3) + 2) : tu1, w1);
      sts16(a ? tu4 : tu2, ba);
      const uint32_t w2 = pk_bf(v[8 + 2 * a], v[9 + 2 * a]);
      sts32((a ? tcl : tcg) - 128 * a - 2, aa);
      sts32((a ? tcl : tcf) - 128 * a + CP + 2, aa);
      sts32(tcl - 128 * a + CP - 2, ba);
      sts16((a ? tpa : tpaf) - 8 * a, w2); sts16((a ? tpa : tpaf) - 8 * a + CP + 2, w2);
      sts16(a ? tm3 : tm1, lo ? w2 >> 16 : w1); sts16(a ? tm2 - (lo ? 8 : 16) : tm2, lo ? w2 >> 16 : ba);
      if (a == 0 && fix && !lo) sts32(sT + T_D + CP + 92, aa);
    }
  }

  if (gater) {
    float s01[4] = {0.f, 0.f, 0.f, 0.f}, s23[4] = {0.f, 0.f, 0.f, 0.f};
    const uint32_t one = 0x3F803F80u;
#define GMMA(S, A, B, W) mma16816bf(S, bmul(A.x, W.x), bmul(B.x, W.x), bmul(A.y, W.y), bmul(B.y, W.y), one, one); \
                         mma16816bf(S, bmul(A.z, W.z), bmul(B.z, W.z), bmul(A.w, W.w), bmul(B.w, W.w), one, one);
    GMMA(s01, gx[0], gx[2], gw0) GMMA(s23, gx[4], gx[6], gw0) GMMA(s01, gx[1], gx[3], gw1) GMMA(s23, gx[5], gx[7], gw1)
#undef GMMA
    float s = (q & 2) ? ((q & 1) ? s23[2] : s23[0]) : ((q & 1) ? s01[2] : s01[0]);
    s += __shfl_xor_sync(0xFFFFFFFFu, s, 4); s += __shfl_xor_sync(0xFFFFFFFFu, s, 8); s += __shfl_xor_sync(0xFFFFFFFFu, s, 16);
    s = bf_lo(pk_bf(s, 0.f));
    const float gv = __fdividef(1.0f, 1.0f + ex2(s * -1.4426950408889634f));
    const uint32_t gpub = ((epoch + 1) << 16) | (pk_bf(gv, 0.f) & 0xFFFFu);
    if (lane < 4) asm volatile("st.relaxed.gpu.global.u32 [%0], %1;" :: "l"(P.gate + blockIdx.x * 16 + wq * 4 + lane), "r"(gpub) : "memory");
  }
  mbar_wait(barU + 40, 0);
  bar_sync(9 + wg, 128);
  const uint32_t g3 = gL + T_P3 + 190, g5 = gL + T_P5 + 190, g7 = gL + T_P7 + 126, g9 = gL + T_P9 + 126, gD = gL + T_D + 1118;
  const uint32_t sV = sW;
#define PK4(A, B) pk_bf(A[4 * (B)], A[4 * (B) + 1]), pk_bf(A[4 * (B) + 2], A[4 * (B) + 3]), pk_bf(A[4 * (B) + 4], A[4 * (B) + 5]), pk_bf(A[4 * (B) + 6], A[4 * (B) + 7])
#define PUSHV(V, DST, BAR) \
    asm volatile("st.async.shared::cluster.mbarrier::complete_tx::bytes.v4.b32 [%0], {%1,%2,%3,%4}, [%5];" \
      :: "r"(mapa(DST, rank ^ 1)), "r"(V.x), "r"(V.y), "r"(V.z), "r"(V.w), "r"(mapa(BAR, rank ^ 1)) : "memory");
#define ARRIVE(BAR) if ((tid_now() & 31) == 0) asm volatile("mbarrier.arrive.shared::cta.b64 _, [%0];" :: "r"(BAR) : "memory");

  float acc1[32], accA[24], accB[16], accS[16], accT[8];
  uint32_t raw[10];
  const uint64_t dU = mkdesc(sU, U1_PLANE, 128);
  raw_load<7, 514>(raw, gD, -2, hh);
  {
    uint32_t E[12], E2[12];
    load_E(E, ve0, ve1, ve2);
    if (role < 2) load_E(E2, ve0 - 512, ve1 - 512, ve2 - 512);
    dense_group<-1, 3, 2>(acc1, raw, dU);
    dense_load<2, 3>(raw, gD, hh);
    build_V<true>(E, vo8, vo16, vo9);
    if (role < 2) build_V<false>(E2, vo8 - 2048, 0, 0);
    else {
      sts128(sV + l16 + (role & 1) * V5_OFF + 3072, 0, 0, 0, 0);
      if (role == 3 && lane == 0) sts128(sV + V9_OFF + 2 * V9_P, 0, 0, 0, 0);
    }
  }
  dense_group<2, 3, 2>(acc1, raw, dU);
  dense_load<5, 3>(raw, gD, hh);
  dense_group<5, 3, 2>(acc1, raw, dU);
  dense_load<8, 3>(raw, gD, hh);
  asm volatile("fence.proxy.async.shared::cta;" ::: "memory");
  dense_group<8, 3, 2>(acc1, raw, dU);
  dense_load<11, 2>(raw, gD, hh);
  dense_group<11, 2, 2>(acc1, raw, dU);
  dense_load<13, 2>(raw, gD, hh);
  dense_group<13, 2, 2>(acc1, raw, dU);
  dense_load<15, 3>(raw, gD, hh);
  wg_wait<0>();
  redef<28>(acc1);
  dense_group<15, 3, 2>(acc1, raw, dU);
  dense_load<18, 3>(raw, gD, hh);
  dense_group<18, 3, 2>(acc1, raw, dU);
  dense_load<21, 3>(raw, gD, hh);
  bar_sync(9 + wg, 128);
  dense_group<21, 3, 2>(acc1, raw, dU);
  dense_load<24, 3>(raw, gD, hh);
  dense_group<24, 3, 2>(acc1, raw, dU);
  dense_load<27, 3>(raw, gD, hh);
  dense_group<27, 3, 2>(acc1, raw, dU);
  dense_load<30, 2>(raw, gD, hh);
  dense_group<30, 2, 2>(acc1, raw, dU);
  dense_load<32, 2>(raw, gD, hh);
  dense_group<32, 2, 1>(acc1, raw, dU);

  const uint64_t d3 = mkdesc(sV + V3_OFF, 128, 512), d5 = mkdesc(sV + V5_OFF, 128, 512);
  const uint64_t d7 = mkdesc(sV + V7_OFF, 128, V16_P), d9 = mkdesc(sV + V9_OFF, 128, V9_P), d2 = mkdesc(sV + V2_OFF, 128, V16_P);
  uint32_t rb[10];
  raw_load<5>(raw, g3, -2, hh); raw_load<5>(raw + 5, g5, -2, hh);
  raw_load<4>(rb + 1, g3, 3, hh); raw_load<4>(rb + 6, g5, 3, hh);
  rb[0] = cpy(raw[4]); rb[5] = cpy(raw[9]);
  far_group<1, 48, true>(accA, raw, d3, d5);
  raw[0] = cpy(rb[4]); raw[5] = cpy(rb[9]);
  far_group<-1, 48>(accA, rb, d3, d5);
  wg_wait<2>();
  unsigned long long gv;
  asm volatile("ld.relaxed.gpu.global.b64 %0, [%1];" : "=l"(gv) : "l"(P.gate + wg * 512 + rank * 256 + 2 * (tid_now() & 127)) : "memory");
  fence_regs<32>(acc1);
  uint32_t sF, uF, sS3;
  {
    const int ln = tid_now(), mat = (ln >> 3) & 3, r8 = ln & 7;
    const uint32_t uo = (br * 4 + 2 * hh + (mat & 1)) * Y_PLANE + r8 * 16;
    const uint32_t sY = sW + Y_OFF + (1 - (mat >> 1)) * Y_OWN + uo;
    stsm4t(sY, PK4(acc1, 6));
    asm volatile("barrier.cluster.wait.aligned;" ::: "memory");
    __syncwarp();
    stsm4t(sY + 3 * Y_BLK, PK4(acc1, 0)); stsm4t(sY + 2 * Y_BLK, PK4(acc1, 2)); stsm4t(sY + Y_BLK, PK4(acc1, 4));
    {
      const uint4 v = lds128p(!(ln & 16), sW + Y_OFF + (rank ^ 1) * Y_OWN + uo);
      if ((ln & 16) == 0) PUSHV(v, sb + OFF_RAW + wg * Y_OWN + uo, barY + 40)
      ARRIVE(barY + 40)
    }
    raw_load<4>(raw + 1, g3, 7, hh); raw_load<4>(raw + 6, g5, 7, hh);
    far_group<-3, 32, true>(accB, raw, d3, d5);
    asm volatile("fence.proxy.async.shared::cta;" ::: "memory");
    bar_sync(9 + wg, 128);
    if ((ln & 127) == 0) {
      asm volatile("cp.async.bulk.shared::cluster.shared::cta.mbarrier::complete_tx::bytes [%0], [%1], %2, [%3];"
        :: "r"(mapa(sb + OFF_RAW + wg * Y_OWN + Y_BLK, rank ^ 1)), "r"(sW + Y_OFF + (rank ^ 1) * Y_OWN + Y_BLK), "r"(3 * Y_BLK), "r"(mapa(barY, rank ^ 1)) : "memory");
      asm volatile("mbarrier.arrive.shared::cta.b64 _, [%0];" :: "r"(barY) : "memory");
    }
    uF = (br * 4 + (r8 & 3)) * Y_PLANE + (7 - 4 * hh - 2 * (mat & 1) - (r8 >> 2)) * 16;
    sF = sW + F_OFF + (1 - (mat >> 1)) * F_OWN + uF;
    sS3 = (br * 4 + 2 * (r8 & 1) + (mat >> 1)) * Y_PLANE + (7 - 4 * (mat & 1) - (r8 >> 1)) * 16;
  }
  {
    const unsigned tag = (epoch + 1) & 0xFFFFu;
    int it = 0;
    while (((((uint32_t)gv >> 16) != tag) || (((uint32_t)(gv >> 48)) != tag)) && ++it < (1 << 20))
      asm volatile("ld.relaxed.gpu.global.b64 %0, [%1];" : "=l"(gv) : "l"(P.gate + wg * 512 + rank * 256 + 2 * (tid_now() & 127)) : "memory");
  }
  const uint32_t g2 = __byte_perm((uint32_t)gv, (uint32_t)(gv >> 32), 0x5410);
  auto finalize = [&]() {
    uint32_t ya[8], yb[8], f0, f1, ft0, ft1;
    uint4* dst;
    const int tx = tid_now() & 127;
    const uint32_t off = wg * Y_BLK + ((tx >> 2) & 3) * Y_PLANE + (7 - (tx >> 4)) * 16 + (tx & 3) * 4;
    const uint32_t own = sb + OFF_W + Y_OFF + rank * Y_OWN + off, oth = sb + OFF_RAW + off;
    const uint32_t a0 = rank ? oth : own, a1 = rank ? own : oth;
    const uint32_t st0 = rank ? Y_OWN : W_WG, st1 = rank ? W_WG : Y_OWN;
    const uint32_t fown = sb + OFF_W + F_OFF + rank * F_OWN + off, foth = (wg == 1) ? oth + 4 * Y_OWN - Y_BLK : oth + (OFF_FIN - OFF_RAW) - 2 * Y_BLK;
    const uint32_t fst = (wg == 1) ? Y_BLK : 2 * Y_BLK;
    f0 = rank ? foth : fown; f1 = rank ? fown : foth; ft0 = rank ? fst : W_WG; ft1 = rank ? W_WG : fst;
    dst = P.out + (size_t)(wg * 512 + rank * 256 + 2 * tx) * 64 + clus;
    mbar_wait(wg ? barY : barY + 40, 0);
    #pragma unroll
    for (int c = 0; c < 4; c++) {
      ya[c] = lds32(a0 + c * st0); yb[c] = lds32(a0 + c * st0 + 4 * Y_PLANE);
      ya[4 + c] = lds32(a1 + c * st1); yb[4 + c] = lds32(a1 + c * st1 + 4 * Y_PLANE);
    }
    if (wg) {
      mbar_wait(barY + 8 * wg, 0);
      #pragma unroll
      for (int c = 0; c < 4; c++) {
        ya[c] = badd(ya[c], lds32(f0 + c * ft0)); yb[c] = badd(yb[c], lds32(f0 + c * ft0 + 4 * Y_PLANE));
        ya[4 + c] = badd(ya[4 + c], lds32(f1 + c * ft1)); yb[4 + c] = badd(yb[4 + c], lds32(f1 + c * ft1 + 4 * Y_PLANE));
      }
    }
    const uint32_t og = bsub(0x3F803F80u, g2);
    uint32_t o[8];
    #pragma unroll
    for (int c = 0; c < 8; c++) o[c] = badd(bmul(g2, ya[c]), bmul(og, yb[c]));
    if (wg == 0) {
      const uint32_t stg = sb + OFF_U1 + wi * 1024, sw = tx & 4;
      const uint32_t s0 = sw ? 0x7632 : 0x5410, s1 = sw ? 0x5410 : 0x7632, ad = stg + (tx & 31) * 32 + sw * 4;
      sts128(ad, __byte_perm(o[0], o[1], s0), __byte_perm(o[2], o[3], s0), __byte_perm(o[4], o[5], s0), __byte_perm(o[6], o[7], s0));
      sts128(ad ^ 16, __byte_perm(o[0], o[1], s1), __byte_perm(o[2], o[3], s1), __byte_perm(o[4], o[5], s1), __byte_perm(o[6], o[7], s1));
      asm volatile("fence.proxy.async.shared::cta;" ::: "memory");
      __syncwarp();
      if ((tx & 31) == 0) {
        asm volatile("cp.reduce.async.bulk.tensor.2d.global.shared::cta.add.tile.bulk_group [%0, {%2, %3}], [%1];"
          :: "l"(&tmO), "r"(stg), "r"(clus * 8), "r"(wg * 512 + rank * 256 + wq * 64) : "memory");
        asm volatile("cp.async.bulk.commit_group;" ::: "memory");
      }
    } else {
      asm volatile("red.global.add.noftz.v4.bf16x2 [%0], {%1,%2,%3,%4};" :: "l"(dst),
      "r"(__byte_perm(o[0], o[1], 0x5410)), "r"(__byte_perm(o[2], o[3], 0x5410)), "r"(__byte_perm(o[4], o[5], 0x5410)), "r"(__byte_perm(o[6], o[7], 0x5410)) : "memory");
      asm volatile("red.global.add.noftz.v4.bf16x2 [%0], {%1,%2,%3,%4};" :: "l"(dst + 64),
      "r"(__byte_perm(o[0], o[1], 0x7632)), "r"(__byte_perm(o[2], o[3], 0x7632)), "r"(__byte_perm(o[4], o[5], 0x7632)), "r"(__byte_perm(o[6], o[7], 0x7632)) : "memory");
    }
  };
  wg_wait<1>();
  if (wg == 0) finalize();
  fence_regs<24>(accA);
  raw_load<5>(raw, g7, -2, hh); raw_load<5>(raw + 5, g9, -2, hh);
  rb[0] = cpy(raw[4]); rb[5] = cpy(raw[9]);
  const uint32_t f1k = lds32(sT + T_P5 + 64);
  stsm4(sF + Y_BLK, PK4(accA, 4));
  {
    const int ln = tid_now() & 31, df = (ln >> 2) - 2 * (ln & 3);
    const uint32_t b = f1k & 0xFFFFu, dg = (df == 0) ? b : ((df == 1) ? (b << 16) : 0u);
    const Frag f0 = mkfrag(raw, true), f1 = mkfrag(raw + 2, false), f2 = mkfrag(raw + 5, true), f3 = mkfrag(raw + 7, false);
    Frag f4, f5;
    f4.a0 = cpy(hh ? 0u : dg); f4.a1 = cpy(0u); f4.a2 = cpy(0u); f4.a3 = cpy(f4.a0);
    f5.a0 = cpy(hh ? dg : 0u); f5.a1 = cpy(0u); f5.a2 = cpy(0u); f5.a3 = cpy(f5.a0);
    wg_fence();
    far_step<1, 32, true, 2 * V16_P>(accS, f0, d7); far_step<0, 32, false, 2 * V16_P>(accS, f1, d7);
    far_step<1, 32, false, 2 * V16_P>(accS, f2, d9); far_step<0, 32, false, 2 * V16_P>(accS, f3, d9);
    far_step<0, 32>(accS, f4, d2); far_step<1, 32>(accS, f5, d2);
    asm volatile("wgmma.commit_group.sync.aligned;" ::: "memory");
  }
  __syncwarp();
  {
    const uint4 v = lds128p(!(tid_now() & 16), sW + F_OFF + (rank ^ 1) * F_OWN + Y_BLK + uF);
    if ((tid_now() & 16) == 0) PUSHV(v, sb + OFF_RAW + 4 * Y_OWN + wg * Y_BLK + uF, barY + 8)
    ARRIVE(barY + 8)
  }
  wg_wait<1>();
  raw_load<4>(rb + 1, g7, 3, hh); raw_load<4>(rb + 6, g9, 3, hh);
  far_group<-1, 16, true, 2 * V16_P, 2 * V9_P>(accT, rb, d7, d9);
  fence_regs<16>(accB);
  #pragma unroll
  for (int i = 0; i < 16; i++) accA[i] += accB[i];
  stsm4(sF + 3 * Y_BLK, PK4(accA, 0)); stsm4(sF + 2 * Y_BLK, PK4(accA, 2));
  bar_sync(1 + wg * 2 + br, 64);
  uint32_t fp[8];
  const uint32_t aS3 = sW + F_OFF + hh * F_OWN + sS3;
  ldsm4(fp[0], fp[1], fp[2], fp[3], aS3 + 3 * Y_BLK); ldsm4(fp[4], fp[5], fp[6], fp[7], aS3 + 2 * Y_BLK);
  wg_wait<1>();
  fence_regs<16>(accS);
  #pragma unroll
  for (int i = 4; i < 8; i++) { accS[2 * i] += bf_lo(fp[i]); accS[2 * i + 1] += bf_hi(fp[i]); }
  stsm4(aS3 + 2 * Y_BLK, PK4(accS, 2));
  __syncwarp();
  if (hh != rank) { const uint4 v = lds128(aS3 + 2 * Y_BLK); PUSHV(v, sb + OFF_FIN + wg * 2 * Y_BLK + sS3, barY + 16) }
  ARRIVE(barY + 16)
  #pragma unroll
  for (int i = 0; i < 4; i++) { accS[2 * i] += bf_lo(fp[i]); accS[2 * i + 1] += bf_hi(fp[i]); }
  wg_wait<0>();
  fence_regs<8>(accT);
  #pragma unroll
  for (int i = 0; i < 8; i++) accS[i] += accT[i];
  stsm4(aS3 + 3 * Y_BLK, PK4(accS, 0));
  __syncwarp();
  if (hh != rank) { const uint4 v = lds128(aS3 + 3 * Y_BLK); PUSHV(v, sb + OFF_FIN + wg * 2 * Y_BLK + Y_BLK + sS3, barY + 24) }
  ARRIVE(barY + 24)
  if (wg != 0) finalize();
  if (wg == 0 && (tid_now() & 31) == 0) asm volatile("cp.async.bulk.wait_group.read 0;" ::: "memory");
  __syncwarp();
  asm volatile("barrier.cluster.arrive.relaxed.aligned;" ::: "memory");
#undef PK4
#undef PUSHV
#undef ARRIVE
  asm volatile("barrier.cluster.wait.aligned;" ::: "memory");
  if (blockIdx.x == 0 && tid_now() == 0) *P.epoch = epoch + 1;
}

typedef CUresult (*EncodeFn)(CUtensorMap*, CUtensorMapDataType, cuuint32_t, void*, const cuuint64_t*, const cuuint64_t*, const cuuint32_t*,
                             const cuuint32_t*, CUtensorMapInterleave, CUtensorMapSwizzle, CUtensorMapL2promotion, CUtensorMapFloatOOBfill);

}

extern "C" void kernel_launch(void* const* d_in, const int* in_sizes, int n_in, void* d_out, int out_size) {
  static EncodeFn enc = nullptr;
  static unsigned *gate_ptr = nullptr, *epoch_ptr = nullptr;
  if (!enc) {
    cudaGetSymbolAddress((void**)&gate_ptr, g_gate);
    cudaGetSymbolAddress((void**)&epoch_ptr, g_epoch);
    cudaFuncSetAttribute(s4d_kernel, cudaFuncAttributeMaxDynamicSharedMemorySize, SMEM_BYTES);
    void* fn = nullptr; cudaDriverEntryPointQueryResult qr;
    cudaGetDriverEntryPoint("cuTensorMapEncodeTiled", &fn, cudaEnableDefault, &qr);
    enc = (EncodeFn)fn;
  }
  CUtensorMap tm, tmo;
  {
    cuuint64_t gd[2] = {512, 2048}; cuuint64_t gs[1] = {1024}; cuuint32_t box[2] = {8, 256}; cuuint32_t es[2] = {1, 1};
    enc(&tm, CU_TENSOR_MAP_DATA_TYPE_BFLOAT16, 2, d_in[0], gd, gs, box, es, CU_TENSOR_MAP_INTERLEAVE_NONE, CU_TENSOR_MAP_SWIZZLE_NONE,
        CU_TENSOR_MAP_L2_PROMOTION_NONE, CU_TENSOR_MAP_FLOAT_OOB_FILL_NONE);
    box[1] = 64;
    enc(&tmo, CU_TENSOR_MAP_DATA_TYPE_BFLOAT16, 2, d_out, gd, gs, box, es, CU_TENSOR_MAP_INTERLEAVE_NONE, CU_TENSOR_MAP_SWIZZLE_NONE,
        CU_TENSOR_MAP_L2_PROMOTION_NONE, CU_TENSOR_MAP_FLOAT_OOB_FILL_NONE);
  }
  Params P;
  P.u = (const uint4*)d_in[0];
  for (int b = 0; b < 2; b++) {
    P.logA[b] = (const uint32_t*)d_in[1 + 7 * b];
    P.Aim[b] = (const uint32_t*)d_in[2 + 7 * b];
    P.Cre[b] = (const uint32_t*)d_in[3 + 7 * b];
    P.Cim[b] = (const uint32_t*)d_in[4 + 7 * b];
    P.logdt[b] = (const uint16_t*)d_in[5 + 7 * b];
    P.Dsk[b] = (const uint16_t*)d_in[6 + 7 * b];
  }
  P.gw = (const uint4*)d_in[14];
  P.out = (uint4*)d_out;
  P.gate = gate_ptr; P.epoch = epoch_ptr;
  s4d_kernel<<<128, 512, SMEM_BYTES>>>(P, tm, tmo);
}
```

```cpp
#include <cuda_runtime.h>
#include <cuda.h>
#include <cuda_bf16.h>
#include <cuda_fp16.h>
#include <stdint.h>

namespace {

constexpr int U1_PLANE = 1184;
constexpr int U1_CH    = 4 * U1_PLANE + 16;
constexpr int OFF_RAW  = 0;
constexpr int OFF_MISC = 32768;
constexpr int OFF_U1   = OFF_MISC + 384;
constexpr int T_D = 0, T_P3 = 1188, T_P5 = 1448, T_P7 = 1708, T_P9 = 1916, CP = 2112, T_BR = 2 * CP;
constexpr int OFF_T    = OFF_U1 + 4 * U1_CH + 64;
constexpr int R_WARP   = 66 * 128;
constexpr int W_WG     = 4 * R_WARP;
constexpr int OFF_W    = OFF_T + 8 * T_BR;
constexpr int V3_OFF = 0, V5_OFF = 3584, V7_OFF = 7168, V9_OFF = 9472, V2_OFF = 11840, V16_P = 576, V9_P = 592;
constexpr int Y_PLANE  = 160, Y_BLK = 8 * Y_PLANE, Y_OWN = 4 * Y_BLK, Y_OFF = 15360, F_OFF = Y_OFF + 2 * Y_OWN - Y_BLK, F_OWN = 3 * Y_BLK;
constexpr int OFF_FIN  = OFF_W + 4 * W_WG;
constexpr int SMEM_BYTES = OFF_FIN + 4 * 2 * Y_BLK;
static_assert(OFF_T % 128 == 0 && OFF_W % 128 == 0 && W_WG % 128 == 0 && F_OFF + Y_BLK + 2 * F_OWN <= W_WG && 4 * Y_OWN + 4 * Y_BLK <= 32768 && SMEM_BYTES <= 232448, "smem");

__device__ unsigned g_epoch;
__device__ unsigned g_gate[2048];

struct Params {
  const uint4* u;
  const uint32_t* logA[2];
  const uint32_t* Aim[2];
  const uint32_t* Cre[2];
  const uint32_t* Cim[2];
  const uint16_t* logdt[2];
  const uint16_t* Dsk[2];
  const uint4* gw;
  uint4* out;
  unsigned* gate;
  unsigned* epoch;
};

template<int N, int TB> __device__ __forceinline__ void wgmma_rs(float* d, uint32_t a0, uint32_t a1, uint32_t a2, uint32_t a3, uint64_t desc);
template<int N, int TB> __device__ __forceinline__ void wgmma_rs_first(float* d, uint32_t a0, uint32_t a1, uint32_t a2, uint32_t a3, uint64_t desc);
template<> __device__ __forceinline__ void wgmma_rs<64,0>(float* d, uint32_t a0, uint32_t a1, uint32_t a2, uint32_t a3, uint64_t desc) {
  asm volatile("wgmma.mma_async.sync.aligned.m64n64k16.f32.bf16.bf16 {%0,%1,%2,%3,%4,%5,%6,%7,%8,%9,%10,%11,%12,%13,%14,%15,%16,%17,%18,%19,%20,%21,%22,%23,%24,%25,%26,%27,%28,%29,%30,%31}, {%32,%33,%34,%35}, %36, 1, 1, 1, 0;"
    : "+f"(d[0]), "+f"(d[1]), "+f"(d[2]), "+f"(d[3]), "+f"(d[4]), "+f"(d[5]), "+f"(d[6]), "+f"(d[7]), "+f"(d[8]), "+f"(d[9]), "+f"(d[10]), "+f"(d[11]), "+f"(d[12]), "+f"(d[13]), "+f"(d[14]), "+f"(d[15]), "+f"(d[16]), "+f"(d[17]), "+f"(d[18]), "+f"(d[19]), "+f"(d[20]), "+f"(d[21]), "+f"(d[22]), "+f"(d[23]), "+f"(d[24]), "+f"(d[25]), "+f"(d[26]), "+f"(d[27]), "+f"(d[28]), "+f"(d[29]), "+f"(d[30]), "+f"(d[31])
    : "r"(a0), "r"(a1), "r"(a2), "r"(a3), "l"(desc));
}
template<> __device__ __forceinline__ void wgmma_rs<56,0>(float* d, uint32_t a0, uint32_t a1, uint32_t a2, uint32_t a3, uint64_t desc) {
  asm volatile("wgmma.mma_async.sync.aligned.m64n56k16.f32.bf16.bf16 {%0,%1,%2,%3,%4,%5,%6,%7,%8,%9,%10,%11,%12,%13,%14,%15,%16,%17,%18,%19,%20,%21,%22,%23,%24,%25,%26,%27}, {%28,%29,%30,%31}, %32, 1, 1, 1, 0;"
    : "+f"(d[0]), "+f"(d[1]), "+f"(d[2]), "+f"(d[3]), "+f"(d[4]), "+f"(d[5]), "+f"(d[6]), "+f"(d[7]), "+f"(d[8]), "+f"(d[9]), "+f"(d[10]), "+f"(d[11]), "+f"(d[12]), "+f"(d[13]), "+f"(d[14]), "+f"(d[15]), "+f"(d[16]), "+f"(d[17]), "+f"(d[18]), "+f"(d[19]), "+f"(d[20]), "+f"(d[21]), "+f"(d[22]), "+f"(d[23]), "+f"(d[24]), "+f"(d[25]), "+f"(d[26]), "+f"(d[27])
    : "r"(a0), "r"(a1), "r"(a2), "r"(a3), "l"(desc));
}
template<> __device__ __forceinline__ void wgmma_rs<48,1>(float* d, uint32_t a0, uint32_t a1, uint32_t a2, uint32_t a3, uint64_t desc) {
  asm volatile("wgmma.mma_async.sync.aligned.m64n48k16.f32.bf16.bf16 {%0,%1,%2,%3,%4,%5,%6,%7,%8,%9,%10,%11,%12,%13,%14,%15,%16,%17,%18,%19,%20,%21,%22,%23}, {%24,%25,%26,%27}, %28, 1, 1, 1, 1;"
    : "+f"(d[0]), "+f"(d[1]), "+f"(d[2]), "+f"(d[3]), "+f"(d[4]), "+f"(d[5]), "+f"(d[6]), "+f"(d[7]), "+f"(d[8]), "+f"(d[9]), "+f"(d[10]), "+f"(d[11]), "+f"(d[12]), "+f"(d[13]), "+f"(d[14]), "+f"(d[15]), "+f"(d[16]), "+f"(d[17]), "+f"(d[18]), "+f"(d[19]), "+f"(d[20]), "+f"(d[21]), "+f"(d[22]), "+f"(d[23])
    : "r"(a0), "r"(a1), "r"(a2), "r"(a3), "l"(desc));
}
template<> __device__ __forceinline__ void wgmma_rs<32,1>(float* d, uint32_t a0, uint32_t a1, uint32_t a2, uint32_t a3, uint64_t desc) {
  asm volatile("wgmma.mma_async.sync.aligned.m64n32k16.f32.bf16.bf16 {%0,%1,%2,%3,%4,%5,%6,%7,%8,%9,%10,%11,%12,%13,%14,%15}, {%16,%17,%18,%19}, %20, 1, 1, 1, 1;"
    : "+f"(d[0]), "+f"(d[1]), "+f"(d[2]), "+f"(d[3]), "+f"(d[4]), "+f"(d[5]), "+f"(d[6]), "+f"(d[7]), "+f"(d[8]), "+f"(d[9]), "+f"(d[10]), "+f"(d[11]), "+f"(d[12]), "+f"(d[13]), "+f"(d[14]), "+f"(d[15])
    : "r"(a0), "r"(a1), "r"(a2), "r"(a3), "l"(desc));
}
template<> __device__ __forceinline__ void wgmma_rs<16,1>(float* d, uint32_t a0, uint32_t a1, uint32_t a2, uint32_t a3, uint64_t desc) {
  asm volatile("wgmma.mma_async.sync.aligned.m64n16k16.f32.bf16.bf16 {%0,%1,%2,%3,%4,%5,%6,%7}, {%8,%9,%10,%11}, %12, 1, 1, 1, 1;"
    : "+f"(d[0]), "+f"(d[1]), "+f"(d[2]), "+f"(d[3]), "+f"(d[4]), "+f"(d[5]), "+f"(d[6]), "+f"(d[7])
    : "r"(a0), "r"(a1), "r"(a2), "r"(a3), "l"(desc));
}
template<> __device__ __forceinline__ void wgmma_rs_first<64,0>(float* d, uint32_t a0, uint32_t a1, uint32_t a2, uint32_t a3, uint64_t desc) {
  asm volatile("wgmma.mma_async.sync.aligned.m64n64k16.f32.bf16.bf16 {%0,%1,%2,%3,%4,%5,%6,%7,%8,%9,%10,%11,%12,%13,%14,%15,%16,%17,%18,%19,%20,%21,%22,%23,%24,%25,%26,%27,%28,%29,%30,%31}, {%32,%33,%34,%35}, %36, 0, 1, 1, 0;"
    : "=f"(d[0]), "=f"(d[1]), "=f"(d[2]), "=f"(d[3]), "=f"(d[4]), "=f"(d[5]), "=f"(d[6]), "=f"(d[7]), "=f"(d[8]), "=f"(d[9]), "=f"(d[10]), "=f"(d[11]), "=f"(d[12]), "=f"(d[13]), "=f"(d[14]), "=f"(d[15]), "=f"(d[16]), "=f"(d[17]), "=f"(d[18]), "=f"(d[19]), "=f"(d[20]), "=f"(d[21]), "=f"(d[22]), "=f"(d[23]), "=f"(d[24]), "=f"(d[25]), "=f"(d[26]), "=f"(d[27]), "=f"(d[28]), "=f"(d[29]), "=f"(d[30]), "=f"(d[31])
    : "r"(a0), "r"(a1), "r"(a2), "r"(a3), "l"(desc));
}
template<> __device__ __forceinline__ void wgmma_rs_first<48,1>(float* d, uint32_t a0, uint32_t a1, uint32_t a2, uint32_t a3, uint64_t desc) {
  asm volatile("wgmma.mma_async.sync.aligned.m64n48k16.f32.bf16.bf16 {%0,%1,%2,%3,%4,%5,%6,%7,%8,%9,%10,%11,%12,%13,%14,%15,%16,%17,%18,%19,%20,%21,%22,%23}, {%24,%25,%26,%27}, %28, 0, 1, 1, 1;"
    : "=f"(d[0]), "=f"(d[1]), "=f"(d[2]), "=f"(d[3]), "=f"(d[4]), "=f"(d[5]), "=f"(d[6]), "=f"(d[7]), "=f"(d[8]), "=f"(d[9]), "=f"(d[10]), "=f"(d[11]), "=f"(d[12]), "=f"(d[13]), "=f"(d[14]), "=f"(d[15]), "=f"(d[16]), "=f"(d[17]), "=f"(d[18]), "=f"(d[19]), "=f"(d[20]), "=f"(d[21]), "=f"(d[22]), "=f"(d[23])
    : "r"(a0), "r"(a1), "r"(a2), "r"(a3), "l"(desc));
}
template<> __device__ __forceinline__ void wgmma_rs_first<32,1>(float* d, uint32_t a0, uint32_t a1, uint32_t a2, uint32_t a3, uint64_t desc) {
  asm volatile("wgmma.mma_async.sync.aligned.m64n32k16.f32.bf16.bf16 {%0,%1,%2,%3,%4,%5,%6,%7,%8,%9,%10,%11,%12,%13,%14,%15}, {%16,%17,%18,%19}, %20, 0, 1, 1, 1;"
    : "=f"(d[0]), "=f"(d[1]), "=f"(d[2]), "=f"(d[3]), "=f"(d[4]), "=f"(d[5]), "=f"(d[6]), "=f"(d[7]), "=f"(d[8]), "=f"(d[9]), "=f"(d[10]), "=f"(d[11]), "=f"(d[12]), "=f"(d[13]), "=f"(d[14]), "=f"(d[15])
    : "r"(a0), "r"(a1), "r"(a2), "r"(a3), "l"(desc));
}
template<> __device__ __forceinline__ void wgmma_rs_first<16,1>(float* d, uint32_t a0, uint32_t a1, uint32_t a2, uint32_t a3, uint64_t desc) {
  asm volatile("wgmma.mma_async.sync.aligned.m64n16k16.f32.bf16.bf16 {%0,%1,%2,%3,%4,%5,%6,%7}, {%8,%9,%10,%11}, %12, 0, 1, 1, 1;"
    : "=f"(d[0]), "=f"(d[1]), "=f"(d[2]), "=f"(d[3]), "=f"(d[4]), "=f"(d[5]), "=f"(d[6]), "=f"(d[7])
    : "r"(a0), "r"(a1), "r"(a2), "r"(a3), "l"(desc));
}

__device__ __forceinline__ void wg_fence()  { asm volatile("wgmma.fence.sync.aligned;" ::: "memory"); }
template<int N> __device__ __forceinline__ void wg_wait() { asm volatile("wgmma.wait_group.sync.aligned %0;" :: "n"(N) : "memory"); }
template<int N> __device__ __forceinline__ void fence_regs(float* d) {
  #pragma unroll
  for (int i = 0; i < N; i++) asm volatile("" : "+f"(d[i]) :: "memory");
}
template<int N> __device__ __forceinline__ void redef(float* d) {
  #pragma unroll
  for (int i = 0; i < N; i++) { float y; asm volatile("mov.b32 %0, %1;" : "=f"(y) : "f"(d[i])); d[i] = y; }
}
__device__ __forceinline__ uint64_t mkdesc(uint32_t addr, uint32_t lbo, uint32_t sbo) {
  return (uint64_t)((addr & 0x3FFFF) >> 4) | ((uint64_t)(lbo >> 4) << 16) | ((uint64_t)(sbo >> 4) << 32);
}
__device__ __forceinline__ void bar_sync(int id, int n) { asm volatile("bar.sync %0, %1;" :: "r"(id), "r"(n) : "memory"); }
__device__ __forceinline__ uint32_t lds32(uint32_t a) { uint32_t v; asm volatile("ld.shared.u32 %0, [%1];" : "=r"(v) : "r"(a)); return v; }
__device__ __forceinline__ uint4 lds128(uint32_t a) { uint4 v; asm volatile("ld.shared.v4.u32 {%0,%1,%2,%3}, [%4];" : "=r"(v.x), "=r"(v.y), "=r"(v.z), "=r"(v.w) : "r"(a)); return v; }
__device__ __forceinline__ uint4 lds128p(bool p, uint32_t a) {
  uint4 v = make_uint4(0, 0, 0, 0);
  asm volatile("{.reg .pred p; setp.ne.u32 p, %5, 0; @p ld.shared.v4.u32 {%0,%1,%2,%3}, [%4];}" : "+r"(v.x), "+r"(v.y), "+r"(v.z), "+r"(v.w) : "r"(a), "r"((uint32_t)p));
  return v;
}
__device__ __forceinline__ uint32_t lds32p(bool p, uint32_t a) {
  uint32_t v;
  asm volatile("{.reg .pred p; setp.ne.u32 p, %2, 0; mov.b32 %0, 0; @p ld.shared.u32 %0, [%1];}" : "=r"(v) : "r"(a), "r"((uint32_t)p));
  return v;
}
__device__ __forceinline__ void ldsm4t(uint32_t& r0, uint32_t& r1, uint32_t& r2, uint32_t& r3, uint32_t a) {
  asm volatile("ldmatrix.sync.aligned.m8n8.x4.trans.shared.b16 {%0,%1,%2,%3}, [%4];" : "=r"(r0), "=r"(r1), "=r"(r2), "=r"(r3) : "r"(a) : "memory");
}
__device__ __forceinline__ void ldsm4(uint32_t& r0, uint32_t& r1, uint32_t& r2, uint32_t& r3, uint32_t a) {
  asm volatile("ldmatrix.sync.aligned.m8n8.x4.shared.b16 {%0,%1,%2,%3}, [%4];" : "=r"(r0), "=r"(r1), "=r"(r2), "=r"(r3) : "r"(a) : "memory");
}
__device__ __forceinline__ void stsm4(uint32_t a, uint32_t r0, uint32_t r1, uint32_t r2, uint32_t r3) {
  asm volatile("stmatrix.sync.aligned.m8n8.x4.shared.b16 [%0], {%1,%2,%3,%4};" :: "r"(a), "r"(r0), "r"(r1), "r"(r2), "r"(r3) : "memory");
}
__device__ __forceinline__ void stsm4t(uint32_t a, uint32_t r0, uint32_t r1, uint32_t r2, uint32_t r3) {
  asm volatile("stmatrix.sync.aligned.m8n8.x4.trans.shared.b16 [%0], {%1,%2,%3,%4};" :: "r"(a), "r"(r0), "r"(r1), "r"(r2), "r"(r3) : "memory");
}
__device__ __forceinline__ void sts16(uint32_t a, uint32_t v) { asm volatile("st.shared.u16 [%0], %1;" :: "r"(a), "r"(v) : "memory"); }
__device__ __forceinline__ void sts32(uint32_t a, uint32_t v) { asm volatile("st.shared.u32 [%0], %1;" :: "r"(a), "r"(v) : "memory"); }
__device__ __forceinline__ void sts128(uint32_t a, uint32_t x, uint32_t y, uint32_t z, uint32_t w) { asm volatile("st.shared.v4.u32 [%0], {%1,%2,%3,%4};" :: "r"(a), "r"(x), "r"(y), "r"(z), "r"(w) : "memory"); }
__device__ __forceinline__ uint32_t mapa(uint32_t a, uint32_t r) { uint32_t v; asm("mapa.shared::cluster.u32 %0, %1, %2;" : "=r"(v) : "r"(a), "r"(r)); return v; }
__device__ __forceinline__ float ex2(float x) { float y; asm("ex2.approx.ftz.f32 %0, %1;" : "=f"(y) : "f"(x)); return y; }
__device__ __forceinline__ float fsin(float x) { float y; asm("sin.approx.ftz.f32 %0, %1;" : "=f"(y) : "f"(x)); return y; }
__device__ __forceinline__ float fcos(float x) { float y; asm("cos.approx.ftz.f32 %0, %1;" : "=f"(y) : "f"(x)); return y; }
__device__ __forceinline__ float bf_lo(uint32_t w) { return __uint_as_float(w << 16); }
__device__ __forceinline__ float bf_hi(uint32_t w) { return __uint_as_float(w & 0xFFFF0000u); }
__device__ __forceinline__ uint32_t pk_h(float lo, float hi) { uint32_t d; asm("cvt.rn.f16x2.f32 %0, %1, %2;" : "=r"(d) : "f"(hi), "f"(lo)); return d; }
__device__ __forceinline__ uint32_t pk_bf(float lo, float hi) { uint32_t d; asm("cvt.rn.bf16x2.f32 %0, %1, %2;" : "=r"(d) : "f"(hi), "f"(lo)); return d; }
__device__ __forceinline__ uint32_t badd(uint32_t a, uint32_t b) { uint32_t d; asm("add.rn.bf16x2 %0, %1, %2;" : "=r"(d) : "r"(a), "r"(b)); return d; }
__device__ __forceinline__ uint32_t bmul(uint32_t a, uint32_t b) { uint32_t d; asm("mul.rn.bf16x2 %0, %1, %2;" : "=r"(d) : "r"(a), "r"(b)); return d; }
__device__ __forceinline__ uint32_t bsub(uint32_t a, uint32_t b) { uint32_t d; asm("sub.rn.bf16x2 %0, %1, %2;" : "=r"(d) : "r"(a), "r"(b)); return d; }
struct C2 { uint32_t r, i; };
__device__ __forceinline__ uint32_t hmul(uint32_t a, uint32_t b) { uint32_t d; asm("mul.rn.f16x2 %0, %1, %2;" : "=r"(d) : "r"(a), "r"(b)); return d; }
__device__ __forceinline__ uint32_t hfma(uint32_t a, uint32_t b, uint32_t c) { uint32_t d; asm("fma.rn.f16x2 %0, %1, %2, %3;" : "=r"(d) : "r"(a), "r"(b), "r"(c)); return d; }
__device__ __forceinline__ uint32_t hfnma(uint32_t a, uint32_t b, uint32_t c) {
  uint32_t d; asm("{.reg .b32 t; neg.f16x2 t, %1; fma.rn.f16x2 %0, t, %2, %3;}" : "=r"(d) : "r"(a), "r"(b), "r"(c)); return d;
}
__device__ __forceinline__ C2 cmul(C2 x, C2 z)  { C2 o; o.r = hfnma(x.i, z.i, hmul(x.r, z.r)); o.i = hfma(x.i, z.r, hmul(x.r, z.i)); return o; }
__device__ __forceinline__ C2 cmulc(C2 x, C2 z) { C2 o; o.r = hfma(x.i, z.i, hmul(x.r, z.r)); o.i = hfnma(x.r, z.i, hmul(x.i, z.r)); return o; }
__device__ __forceinline__ void csq(float& r, float& i) { float t = i * i; float n = fmaf(r, r, -t); i = __uint_as_float(__float_as_uint(r * i) + 0x00800000u); r = n; }

__device__ __forceinline__ uint32_t cpy(uint32_t x) { uint32_t y; asm volatile("mov.b32 %0, %1;" : "=r"(y) : "r"(x)); return y; }
__device__ __forceinline__ void keep(uint32_t& x) { asm volatile("" : "+r"(x)); }
__device__ __forceinline__ int tid_now() { int t; asm volatile("mov.u32 %0, %%tid.x;" : "=r"(t)); return t; }
struct Frag { uint32_t a0, a1, a2, a3; };
template<int TOP> __device__ __forceinline__ uint32_t tap_word(uint32_t base, int p, int hh) {
  if (p <= -3 || 8 * p - 7 > TOP) return cpy(0u);
  if (p <= -1) return lds32p(hh, base - 16 * p);
  if (8 * p + 9 > TOP) return lds32p(!hh, base - 16 * p);
  return lds32(base - 16 * p);
}
template<int N, int TOP = 63> __device__ __forceinline__ void raw_load(uint32_t* raw, uint32_t base, int p, int hh) {
  #pragma unroll
  for (int i = 0; i < N; i++) raw[i] = tap_word<TOP>(base, p - 1 + i, hh);
}
__device__ __forceinline__ Frag mkfrag(const uint32_t* r, bool first) { Frag f; f.a0 = r[1]; f.a1 = r[2]; f.a2 = first ? r[0] : cpy(r[0]); f.a3 = cpy(r[1]); return f; }
template<int S> __device__ __forceinline__ void dense_step(float* acc, const Frag& f, uint64_t d0) {
  constexpr int kk = S & 1, m = (S + 1) >> 1;
  constexpr int N = (m < 8) ? 64 : 56;
  if constexpr (S == -1) wgmma_rs_first<64, 0>(acc, f.a0, f.a1, f.a2, f.a3, d0 + (uint64_t)((2 * kk * U1_PLANE + m * 16) >> 4));
  else wgmma_rs<N, 0>(acc, f.a0, f.a1, f.a2, f.a3, d0 + (uint64_t)((2 * kk * U1_PLANE + m * 16) >> 4));
}
template<int S0, int NS> __device__ __forceinline__ void dense_load(uint32_t* raw, uint32_t base, int hh) {
  #pragma unroll
  for (int i = 1; i <= 2 * NS; i++) raw[i] = tap_word<514>(base, 2 * S0 - 1 + i, hh);
}
template<int S0, int NS, int W> __device__ __forceinline__ void dense_group(float* acc, uint32_t* raw, uint64_t d0) {
  Frag f[3];
  #pragma unroll
  for (int i = 0; i < NS; i++) f[i] = mkfrag(raw + 2 * i, i == 0);
  raw[0] = cpy(raw[2 * NS]);
  wg_fence();
  dense_step<S0>(acc, f[0], d0); dense_step<S0 + 1>(acc, f[1], d0);
  if constexpr (NS > 2) dense_step<S0 + 2>(acc, f[2], d0);
  asm volatile("wgmma.commit_group.sync.aligned;" ::: "memory");
  wg_wait<W>();
}
template<int S, int N, bool FIRST = false, int BS = 512> __device__ __forceinline__ void far_step(float* acc, const Frag& f, uint64_t d0) {
  constexpr int fl = (S >= 0) ? (S / 2) : -((1 - S) / 2);
  if constexpr (FIRST) wgmma_rs_first<N, 1>(acc, f.a0, f.a1, f.a2, f.a3, d0 + (uint64_t)(((-fl) * BS + (S & 1) * 256) >> 4));
  else wgmma_rs<N, 1>(acc, f.a0, f.a1, f.a2, f.a3, d0 + (uint64_t)(((-fl) * BS + (S & 1) * 256) >> 4));
}
template<int S, int N, bool FIRST = false, int BS = 512, int BS2 = BS> __device__ __forceinline__ void far_group(float* acc, const uint32_t* raw, uint64_t da, uint64_t db) {
  const Frag f0 = mkfrag(raw, true), f1 = mkfrag(raw + 2, false), f2 = mkfrag(raw + 5, true), f3 = mkfrag(raw + 7, false);
  wg_fence();
  far_step<S, N, FIRST, BS>(acc, f0, da); far_step<S - 1, N, false, BS>(acc, f1, da); far_step<S, N, false, BS2>(acc, f2, db); far_step<S - 1, N, false, BS2>(acc, f3, db);
  asm volatile("wgmma.commit_group.sync.aligned;" ::: "memory");
}
__device__ __forceinline__ void mma16816bf(float* c, uint32_t a0, uint32_t a1, uint32_t a2, uint32_t a3, uint32_t b0, uint32_t b1) {
  asm volatile("mma.sync.aligned.m16n8k16.row.col.f32.bf16.bf16.f32 {%0,%1,%2,%3}, {%4,%5,%6,%7}, {%8,%9}, {%0,%1,%2,%3};"
    : "+f"(c[0]), "+f"(c[1]), "+f"(c[2]), "+f"(c[3]) : "r"(a0), "r"(a1), "r"(a2), "r"(a3), "r"(b0), "r"(b1));
}
__device__ __forceinline__ void mbar_wait(uint32_t bar, uint32_t parity) {
  uint32_t ok = 0; int it = 0;
  do {
    asm volatile("{.reg .pred p; mbarrier.try_wait.parity.shared::cta.b64 p, [%1], %2, 20000; selp.u32 %0, 1, 0, p;}" : "=r"(ok) : "r"(bar), "r"(parity) : "memory");
  } while (!ok && ++it < (1 << 16));
}
__device__ __forceinline__ void cexp2(float& r, float& i, float e, float x) {
  const float k = __fadd_rn(fmaf(x, 0.15915494309189535f, 12582912.f), -12582912.f);
  const float m = ex2(e), a = fmaf(k, -6.283185307179586f, x);
  r = m * fcos(a); i = m * fsin(a);
}
__device__ __forceinline__ void mma16816h(uint32_t* c, uint32_t a0, uint32_t a1, uint32_t a2, uint32_t a3, uint32_t b0, uint32_t b1) {
  asm("mma.sync.aligned.m16n8k16.row.col.f16.f16.f16.f16 {%0,%1}, {%2,%3,%4,%5}, {%6,%7}, {%0,%1};"
    : "+r"(c[0]), "+r"(c[1]) : "r"(a0), "r"(a1), "r"(a2), "r"(a3), "r"(b0), "r"(b1));
}
__device__ __forceinline__ float h_lo(uint32_t w) { return __half2float(__ushort_as_half((unsigned short)(w & 0xFFFFu))); }
__device__ __forceinline__ float h_hi(uint32_t w) { return __half2float(__ushort_as_half((unsigned short)(w >> 16))); }

__device__ __forceinline__ void load_E(uint32_t* E, uint32_t a0, uint32_t a1, uint32_t a2, int lane) {
  const uint4 e = lds128(a2);
  E[8] = e.x; E[9] = e.y; E[10] = e.z; E[11] = e.w;
  #pragma unroll
  for (int i = 0; i < 4; i++) E[4 + i] = __shfl_up_sync(0xFFFFFFFFu, E[8 + i], 1);
  E[2] = __shfl_up_sync(0xFFFFFFFFu, E[10], 2); E[3] = __shfl_up_sync(0xFFFFFFFFu, E[11], 2);
  asm volatile("{.reg .pred p; setp.lt.s32 p, %3, 2; @p ld.shared.v2.u32 {%0,%1}, [%2+8];}" : "+r"(E[2]), "+r"(E[3]) : "r"(a0), "r"(lane));
  asm volatile("{.reg .pred p; setp.eq.s32 p, %5, 0; @p ld.shared.v4.u32 {%0,%1,%2,%3}, [%4];}" : "+r"(E[4]), "+r"(E[5]), "+r"(E[6]), "+r"(E[7]) : "r"(a1), "r"(lane));
}
template<bool FULL> __device__ __forceinline__ void build_V(const uint32_t* E, uint32_t o8, uint32_t o16, uint32_t o9) {
  uint32_t O[11], Q[11], R[10], V3[11], V5[10];
  #pragma unroll
  for (int n = FULL ? 3 : 4; n <= 10; n++) { O[n] = __byte_perm(E[n - 1], E[n], 0x5432); Q[n] = badd(O[n], E[n - 1]); }
  #pragma unroll
  for (int n = FULL ? 4 : 5; n <= (FULL ? 9 : 8); n++) R[n] = badd(Q[n], Q[n - 1]);
  #pragma unroll
  for (int n = FULL ? 4 : 7; n <= 10; n++) V3[n] = badd(Q[n], O[n - 1]);
  #pragma unroll
  for (int n = 5; n <= (FULL ? 9 : 8); n++) V5[n] = badd(E[n], R[n]);
  sts128(o8 + V3_OFF, V3[7], V3[8], V3[9], V3[10]);
  sts128(o8 + V5_OFF, V5[5], V5[6], V5[7], V5[8]);
  if (FULL) {
    sts128(o16 + V7_OFF, badd(R[6], V3[4]), badd(R[7], V3[5]), badd(R[8], V3[6]), badd(R[9], V3[7]));
    sts128(o9, badd(V5[6], R[4]), badd(V5[7], R[5]), badd(V5[8], R[6]), badd(V5[9], R[7]));
    sts128(o16 + V2_OFF, Q[7], Q[8], Q[9], Q[10]);
  }
}

__global__ void __cluster_dims__(2, 1, 1) __launch_bounds__(512, 1)
s4d_kernel(const __grid_constant__ Params P, const __grid_constant__ CUtensorMap tmU, const __grid_constant__ CUtensorMap tmO) {
  extern __shared__ __align__(256) uint8_t smem[];
  const int tid = threadIdx.x, lane = tid & 31, wi = __shfl_sync(0xFFFFFFFFu, tid >> 5, 0), wg = wi >> 2, wq = wi & 3;
  const int br = wq >> 1, hh = wq & 1;
  const unsigned pch = blockIdx.x * 4 + wg, pw = pch * 64 + hh * 32;
  const uint32_t wLA = __ldg(P.logA[br] + pw + lane), wAI = __ldg(P.Aim[br] + pw + lane);
  const uint32_t wDT = __ldg(P.logdt[br] + pch);
  const uint32_t wCR = __ldg(P.Cre[br] + pw + lane), wCI = __ldg(P.Cim[br] + pw + lane);
  const uint32_t wCR2 = __ldg(P.Cre[br] + (pw ^ 32) + lane), wCI2 = __ldg(P.Cim[br] + (pw ^ 32) + lane);
  const uint32_t wDS = __ldg(P.Dsk[br] + pch);
  unsigned epoch;
  asm volatile("ld.relaxed.gpu.global.u32 %0, [%1];" : "=r"(epoch) : "l"(P.epoch) : "memory");
  const uint32_t sb = (uint32_t)__cvta_generic_to_shared(smem);
  const int g = lane >> 2, q = lane & 3;
  const int rank = blockIdx.x & 1, clus = blockIdx.x >> 1;
  const uint32_t barU = sb + OFF_MISC, barY = sb + OFF_MISC + 8, junk = sb + OFF_MISC + 128;
  const bool gater = wg == 3;

  const uint32_t sT = sb + OFF_T + (wg * 2 + br) * T_BR;
  const uint32_t sU = sb + OFF_U1 + wg * U1_CH;
  const uint32_t sW = sb + OFF_W + wg * W_WG;
  const uint32_t sR = sW + wq * R_WARP;
  const uint32_t l4 = lane * 4, l16 = lane * 16;
  const uint32_t we = sR + l4, wo = sR + (l4 ^ 64);
  #pragma unroll
  for (int k = 0; k < 4; k++) sts128(sT + hh * CP + l16 + k * 512, 0, 0, 0, 0);
  if (lane < 10) {
    sts128(sU + wq * U1_PLANE + 1024 + l16, 0, 0, 0, 0);
    if (lane < 4) sts128(sT + hh * CP + 2048 + l16, 0, 0, 0, 0);
  }
  sts32(we + 48 * 128, 0x3C003C00u); sts32(we + 56 * 128, 0u);
  const bool lo = q < 2, fix = (hh == 0) && !(lane & 29);
  const uint32_t jk = sR + 2560, q64 = (lane & 1) * 64;
  const uint32_t c0 = sT + T_D + 606 - 256 * hh - l4 - 4 * q, p3 = sT + T_P3 + 190 - 32 * hh - 2 * g - q64;
  uint32_t tb0 = sT + T_D + 1116 - 256 * hh - l4;
  uint32_t tcl = lo ? c0 : jk + ((c0 + 12) & 127u);
  const uint32_t pa = sT + ((lane & 4) ? T_P7 + 126 : T_P9 + 128) - 16 * hh - (g & 6) - q64;
  uint32_t tpa = lo ? pa : jk + ((pa + 32) & 127u);
  uint32_t tu2 = lo ? c0 - 4 : p3, tu4 = tu2 - (lo ? 128 : 16);
  uint32_t tu1 = tu2 + (lo ? 6 : (T_P5 - T_P3) + 2);
  uint32_t tm1 = lo ? pa - 32 : p3 + (T_P5 - T_P3) + CP + 4, tm2 = lo ? pa - 32 + CP + 2 : p3 + CP + 2;
  uint32_t tm3 = tm1 - (lo ? 8 : 16);
  uint32_t tcf = tcl, tcg = tcl, tpaf = tpa;
  if (fix) {
    tu1 = sT + (lo ? T_D + CP + 2 * (560 - 256) : T_D + 96);
    tpaf = sT + (lo ? T_P5 + 64 : T_P9);
    tcf = lo ? jk + 2 : sT + T_D + 94;
    if (!lo) { tm1 = sT + T_D + 90; tcg = sT + T_D + 94; }
  }
  const int rw = (lane & 7) - 4 * rank;
  uint32_t xdst = sb + OFF_U1 + (63 - 8 * ((wi - 4) & 7)) * 16 + (lane >> 3) * U1_PLANE + rw * U1_CH;
  if ((unsigned)rw >= 4u) xdst = junk + 128 + (xdst & 127u);
  const uint32_t xsrc = sb + OFF_RAW + ((wi - 4) & 7) * 4096 + l16;
  uint32_t gL = sT - 32 * hh + ((lane & 4) ? 0 : CP + 2) - 2 * g + 4 * q;
  const int role = (wq + wg) & 3;
  uint32_t ve2 = sU + (63 - 8 * role) * 16 + q * U1_PLANE - g * 16;
  uint32_t ve1 = ve2 + (q == 0 ? 3 * U1_PLANE + 16 : -U1_PLANE), ve0 = ve2 + (lo ? 2 * U1_PLANE + 16 : -2 * U1_PLANE);
  const uint32_t vo8 = sW + (5 - role) * 512 + l16;
  uint32_t vo16 = sW + (1 - (role >> 1)) * 2 * V16_P + (role & 1) * 256 + q64 * (V16_P / 64) + (lane >> 1) * 16;
  uint32_t vo9 = vo16 + V9_OFF + (1 - (role >> 1)) * 2 * (V9_P - V16_P) + ((lane & 1) ? 16 - V16_P : V9_P);
  if (lane == 31 && (role & 1)) vo9 = (role == 3) ? junk : sW + V9_OFF;
  keep(ve0); keep(ve1); keep(ve2); keep(vo16); keep(vo9);
  keep(tb0); keep(tcl); keep(tpa); keep(tu1); keep(tu2); keep(tu4); keep(tcf); keep(tcg); keep(tpaf); keep(tm1); keep(tm2); keep(tm3); keep(xdst); keep(gL);

  asm volatile("fence.proxy.async.shared::cta;" ::: "memory");
  __syncwarp();
  if (lane == 0 && gater) {
    asm volatile("cp.async.bulk.global.shared::cta.bulk_group [%0], [%1], 2048;" :: "l"(P.out + (size_t)(blockIdx.x * 16 + wq * 4) * 64), "r"(sT + hh * CP) : "memory");
    asm volatile("cp.async.bulk.global.shared::cta.bulk_group [%0], [%1], 2048;" :: "l"(P.out + (size_t)(blockIdx.x * 16 + wq * 4 + 2) * 64), "r"(sT + hh * CP) : "memory");
    asm volatile("cp.async.bulk.commit_group;" ::: "memory");
  }
  if (tid == 480) {
    asm volatile("prefetch.tensormap [%0];" :: "l"(&tmU) : "memory");
    asm volatile("prefetch.tensormap [%0];" :: "l"(&tmO) : "memory");
    asm volatile("mbarrier.init.shared::cta.b64 [%0], 1;" :: "r"(barU) : "memory");
    asm volatile("mbarrier.init.shared::cta.b64 [%0], 8;" :: "r"(barU + 40) : "memory");
    asm volatile("mbarrier.init.shared::cta.b64 [%0], 17;" :: "r"(barY + 24) : "memory");
    asm volatile("mbarrier.init.shared::cta.b64 [%0], 17;" :: "r"(barY + 40) : "memory");
    asm volatile("mbarrier.arrive.expect_tx.shared::cta.b64 _, [%0], %1;" :: "r"(barY + 40), "r"(4096) : "memory");
    asm volatile("mbarrier.init.shared::cta.b64 [%0], 5;" :: "r"(barY) : "memory");
    asm volatile("mbarrier.init.shared::cta.b64 [%0], 17;" :: "r"(barY + 8) : "memory");
    asm volatile("mbarrier.init.shared::cta.b64 [%0], 17;" :: "r"(barY + 16) : "memory");
    asm volatile("mbarrier.arrive.expect_tx.shared::cta.b64 _, [%0], %1;" :: "r"(barU), "r"(32768) : "memory");
    asm volatile("mbarrier.arrive.expect_tx.shared::cta.b64 _, [%0], %1;" :: "r"(barY), "r"(12 * Y_BLK) : "memory");
    asm volatile("mbarrier.arrive.expect_tx.shared::cta.b64 _, [%0], %1;" :: "r"(barY + 8), "r"(4096) : "memory");
    asm volatile("mbarrier.arrive.expect_tx.shared::cta.b64 _, [%0], %1;" :: "r"(barY + 16), "r"(4096) : "memory");
    asm volatile("mbarrier.arrive.expect_tx.shared::cta.b64 _, [%0], %1;" :: "r"(barY + 24), "r"(4096) : "memory");
    asm volatile("fence.mbarrier_init.release.cluster;" ::: "memory");
  }
  __syncwarp();
  asm volatile("barrier.cluster.arrive.relaxed.aligned;" ::: "memory");
  if (wi == 15) {
    asm volatile("barrier.cluster.wait.aligned;" ::: "memory");
    if (lane == 0) {
      #pragma unroll
      for (int k = 0; k < 4; k++)
        asm volatile("cp.async.bulk.tensor.2d.shared::cluster.global.mbarrier::complete_tx::bytes.multicast::cluster [%0], [%1, {%3, %4}], [%2], %5;"
          :: "r"(sb + OFF_RAW + (rank * 1024 + k * 256) * 16), "l"(&tmU), "r"(barU), "r"(clus * 8), "r"(rank * 1024 + k * 256), "h"((unsigned short)3) : "memory");
    }
    __syncwarp();
  }

  const float dt = bf_lo(pk_bf(ex2(bf_lo(wDT) * 1.4426950408889634f), 0.f));
  float csc, tsc;
  {
    uint32_t m = __vmaxu2(__vmaxu2(wCR & 0x7FFF7FFFu, wCI & 0x7FFF7FFFu), __vmaxu2(wCR2 & 0x7FFF7FFFu, wCI2 & 0x7FFF7FFFu));
    m = max(m & 0xFFFFu, m >> 16);
    m = __reduce_max_sync(0xFFFFFFFFu, m);
    int k = 134 - (int)(m >> 7);
    k = min(max(k, -126), 126);
    csc = __uint_as_float((uint32_t)(k + 127) << 23);
    tsc = 2.0f * dt * __uint_as_float((uint32_t)(127 - k) << 23);
  }
  {
    const uint32_t Ab = pk_bf(ex2(bf_lo(wLA) * 1.4426950408889634f), ex2(bf_hi(wLA) * 1.4426950408889634f));
    const float ndt = dt * -1.4426950408889634f;
    const float ea = bf_lo(Ab) * ndt, eb = bf_hi(Ab) * ndt, ta = bf_lo(wAI) * dt, tb = bf_hi(wAI) * dt;
    float ra, ia, rb, ib;
    cexp2(ra, ia, ea, ta); cexp2(rb, ib, eb, tb);
#define PK1 C2{pk_h(ra, rb), pk_h(ia, ib)}
#define SQ1 csq(ra, ia); csq(rb, ib);
#define PUT(T, G, V) { sts32(((G) & 1 ? wo : we) + ((T) * 16 + (G)) * 128, (V).r); sts32(((G) & 1 ? wo : we) + ((T) * 16 + 8 + (G)) * 128, (V).i); }
    C2 H0[8], X[8], H1[8], H2[5];
    H0[0] = C2{pk_h(bf_lo(wCR) * csc, bf_hi(wCR) * csc), pk_h(bf_lo(wCI) * -csc, bf_hi(wCI) * -csc)}; PUT(0, 0, H0[0])
    const C2 m1 = PK1; H0[1] = cmulc(H0[0], m1); PUT(0, 1, H0[1])
    SQ1 const C2 m2 = PK1;
    H0[2] = cmulc(H0[0], m2); PUT(0, 2, H0[2]) H0[3] = cmulc(H0[1], m2); PUT(0, 3, H0[3])
    SQ1 const C2 m4 = PK1;
    H0[4] = cmulc(H0[0], m4); PUT(0, 4, H0[4]) H0[5] = cmulc(H0[1], m4); PUT(0, 5, H0[5])
    SQ1 X[1] = PK1; PUT(3, 1, X[1])
    H0[6] = cmulc(H0[2], m4); PUT(0, 6, H0[6]) H0[7] = cmulc(H0[3], m4); PUT(0, 7, H0[7])
    SQ1 X[2] = PK1; PUT(3, 2, X[2])
    X[3] = cmul(X[2], X[1]); PUT(3, 3, X[3])
    SQ1 X[4] = PK1; PUT(3, 4, X[4])
    X[5] = cmul(X[4], X[1]); PUT(3, 5, X[5]) X[6] = cmul(X[4], X[2]); PUT(3, 6, X[6])
    SQ1 const C2 Z = PK1;
    sts32(we + 64 * 128, Z.r); sts32(we + 65 * 128, Z.i);
    X[7] = cmul(X[6], X[1]); PUT(3, 7, X[7])
    SQ1 SQ1 const C2 m256 = PK1;
    H1[0] = cmulc(H0[0], m256); PUT(1, 0, H1[0]) H1[1] = cmulc(H0[2], m256); PUT(1, 1, H1[1])
    SQ1 const C2 m512 = PK1;
    H1[2] = cmulc(H0[4], m256); PUT(1, 2, H1[2]) H1[3] = cmulc(H0[6], m256); PUT(1, 3, H1[3])
    SQ1 const C2 m1k = PK1;
    H1[4] = cmulc(H0[0], m512); PUT(1, 4, H1[4]) H1[5] = cmulc(H0[4], m512); PUT(1, 5, H1[5])
    H1[6] = cmulc(H1[0], m512); PUT(1, 6, H1[6]) H1[7] = cmulc(H1[2], m512); PUT(1, 7, H1[7])
    H2[0] = cmulc(H0[0], m1k); PUT(2, 0, H2[0]) H2[1] = cmulc(H1[0], m1k); PUT(2, 1, H2[1])
    H2[2] = cmulc(H1[4], m1k); PUT(2, 2, H2[2]) H2[3] = cmulc(H1[6], m1k); PUT(2, 3, H2[3])
    H2[4] = cmulc(H2[0], m1k); PUT(2, 4, H2[4])
#undef PUT
#undef PK1
#undef SQ1
  }
  if (wi != 15) asm volatile("barrier.cluster.wait.aligned;" ::: "memory");
  __syncwarp();
  uint32_t cD[2][3][2];
  #pragma unroll
  for (int i = 0; i < 12; i++) (&cD[0][0][0])[i] = 0u;
  {
    #pragma unroll
    for (int h2 = 0; h2 < 2; h2++) {
      const uint32_t r0 = sR + g * 128 + 16 * ((q + 4 * h2) ^ (4 * (g & 1))), zb = sR + 64 * 128 + 16 * (q + 4 * h2);
      const uint4 Xr = lds128(r0 + 48 * 128), Xi = lds128(r0 + 56 * 128), Zr = lds128(zb), Zi = lds128(zb + 128);
      const uint4 H0r = lds128(r0), H0i = lds128(r0 + 8 * 128), H1r = lds128(r0 + 16 * 128), H1i = lds128(r0 + 24 * 128);
      const uint4 H2r = lds128p(g < 6, r0 + 32 * 128), H2i = lds128p(g < 6, r0 + 40 * 128);
#define KSTEP(E, F) { \
      const C2 za = C2{Zr.E, Zi.E}, zc = C2{Zr.F, Zi.F}, a0 = C2{Xr.E, Xi.E}, c0 = C2{Xr.F, Xi.F}; \
      const C2 a1 = cmul(a0, za), c1 = cmul(c0, zc), a2 = cmul(a1, za), c2 = cmul(c1, zc), a3 = cmul(a2, za), c3 = cmul(c2, zc); \
      mma16816h(cD[0][0], a0.r, a1.r, c0.r, c1.r, H0r.E, H0r.F); mma16816h(cD[0][1], a0.r, a1.r, c0.r, c1.r, H1r.E, H1r.F); \
      mma16816h(cD[0][2], a0.r, a1.r, c0.r, c1.r, H2r.E, H2r.F); \
      mma16816h(cD[0][0], a0.i, a1.i, c0.i, c1.i, H0i.E, H0i.F); mma16816h(cD[0][1], a0.i, a1.i, c0.i, c1.i, H1i.E, H1i.F); \
      mma16816h(cD[0][2], a0.i, a1.i, c0.i, c1.i, H2i.E, H2i.F); \
      mma16816h(cD[1][0], a2.r, a3.r, c2.r, c3.r, H0r.E, H0r.F); mma16816h(cD[1][1], a2.r, a3.r, c2.r, c3.r, H1r.E, H1r.F); \
      mma16816h(cD[1][2], a2.r, a3.r, c2.r, c3.r, H2r.E, H2r.F); \
      mma16816h(cD[1][0], a2.i, a3.i, c2.i, c3.i, H0i.E, H0i.F); mma16816h(cD[1][1], a2.i, a3.i, c2.i, c3.i, H1i.E, H1i.F); \
      mma16816h(cD[1][2], a2.i, a3.i, c2.i, c3.i, H2i.E, H2i.F); }
      KSTEP(x, y) KSTEP(z, w)
#undef KSTEP
    }
  }
  __syncwarp();
  uint4 gx[8], gw0, gw1;
  if (gater) {
    const size_t grow = (size_t)(blockIdx.x * 16 + wq * 4) * 64 + lane;
    #pragma unroll
    for (int r = 0; r < 8; r++) gx[r] = __ldg(P.u + grow + r * 32);
    gw0 = __ldg(P.gw + lane); gw1 = __ldg(P.gw + 32 + lane);
    if (lane == 0) asm volatile("cp.async.bulk.wait_group 0;" ::: "memory");
    __syncwarp();
  } else if (wg) {
    mbar_wait(barU, 0);
    #pragma unroll
    for (int k = 0; k < 8; k += 4) {
      uint32_t r[4][4];
      #pragma unroll
      for (int j = 0; j < 4; j++) ldsm4t(r[j][0], r[j][1], r[j][2], r[j][3], xsrc + (k + j) * 512);
      #pragma unroll
      for (int j = 0; j < 4; j++) stsm4(xdst - 16 * (k + j), r[j][0], r[j][1], r[j][2], r[j][3]);
    }
    asm volatile("fence.proxy.async.shared::cta;" ::: "memory");
    __syncwarp();
    if (lane == 0) asm volatile("mbarrier.arrive.shared::cta.b64 _, [%0];" :: "r"(barU + 40) : "memory");
  }
  asm volatile("barrier.cluster.arrive.relaxed.aligned;" ::: "memory");
  float v[12];
  {
    const uint32_t sO = sW + (wq ^ 1) * R_WARP + lane * 16, sS = sR + lane * 16;
#define XCH(SND, KEEP) \
    sts128(sS, cD[SND][0][0], cD[SND][0][1], cD[SND][1][0], cD[SND][1][1]); sts32(sR + 512 + l4, cD[SND][2][0]); sts32(sR + 640 + l4, cD[SND][2][1]); \
    bar_sync(1 + wg * 2 + br, 64); \
    { const uint4 o = lds128(sO), p = make_uint4(lds32(sO - l16 + 512 + l4), lds32(sO - l16 + 640 + l4), 0u, 0u); const uint32_t w[6] = {o.x, o.y, o.z, o.w, p.x, p.y}; \
      _Pragma("unroll") for (int k = 0; k < 6; k++) { \
        v[2 * k] = (h_lo(cD[KEEP][k >> 1][k & 1]) + h_lo(w[k])) * tsc; v[2 * k + 1] = (h_hi(cD[KEEP][k >> 1][k & 1]) + h_hi(w[k])) * tsc; } }
    if (hh) { XCH(0, 1) } else { XCH(1, 0) }
#undef XCH
  }
  {
    if (hh == 0 && lane == 0) v[0] += bf_lo(wDS);
    #pragma unroll
    for (int a = 0; a < 2; a++) {
      const uint32_t w0 = pk_bf(v[2 * a + 1], v[2 * a]);
      sts32(tb0 - 128 * a, w0);
      sts16(tb0 - 128 * a + CP + 4, w0 >> 16);
      sts16(tb0 - 128 * a + CP + 2, w0);
      const uint32_t w1 = pk_bf(v[4 + 2 * a], v[5 + 2 * a]);
      const uint32_t aa = __byte_perm(w1, 0, 0x1010), ba = __byte_perm(w1, 0, 0x1032);
      sts16(a ? tu4 + (lo ? 6 : (T_P5 - T_P3) + 2) : tu1, w1);
      sts16(a ? tu4 : tu2, ba);
      const uint32_t w2 = pk_bf(v[8 + 2 * a], v[9 + 2 * a]);
      sts32((a ? tcl : tcg) - 128 * a - 2, aa);
      sts32((a ? tcl : tcf) - 128 * a + CP + 2, aa);
      sts32(tcl - 128 * a + CP - 2, ba);
      sts16((a ? tpa : tpaf) - 8 * a, w2); sts16((a ? tpa : tpaf) - 8 * a + CP + 2, w2);
      sts16(a ? tm3 : tm1, lo ? w2 >> 16 : w1); sts16(a ? tm2 - (lo ? 8 : 16) : tm2, lo ? w2 >> 16 : ba);
      if (a == 0 && fix && !lo) sts32(sT + T_D + CP + 92, aa);
    }
  }

  if (gater) {
    float s01[4] = {0.f, 0.f, 0.f, 0.f}, s23[4] = {0.f, 0.f, 0.f, 0.f};
    const uint32_t one = 0x3F803F80u;
#define GMMA(S, A, B, W) mma16816bf(S, bmul(A.x, W.x), bmul(B.x, W.x), bmul(A.y, W.y), bmul(B.y, W.y), one, one); \
                         mma16816bf(S, bmul(A.z, W.z), bmul(B.z, W.z), bmul(A.w, W.w), bmul(B.w, W.w), one, one);
    GMMA(s01, gx[0], gx[2], gw0) GMMA(s23, gx[4], gx[6], gw0) GMMA(s01, gx[1], gx[3], gw1) GMMA(s23, gx[5], gx[7], gw1)
#undef GMMA
    float s = (q & 2) ? ((q & 1) ? s23[2] : s23[0]) : ((q & 1) ? s01[2] : s01[0]);
    s += __shfl_xor_sync(0xFFFFFFFFu, s, 4); s += __shfl_xor_sync(0xFFFFFFFFu, s, 8); s += __shfl_xor_sync(0xFFFFFFFFu, s, 16);
    s = bf_lo(pk_bf(s, 0.f));
    const float gv = __fdividef(1.0f, 1.0f + ex2(s * -1.4426950408889634f));
    const uint32_t gpub = ((epoch + 1) << 16) | (pk_bf(gv, 0.f) & 0xFFFFu);
    if (lane < 4) asm volatile("st.relaxed.gpu.global.u32 [%0], %1;" :: "l"(P.gate + blockIdx.x * 16 + wq * 4 + lane), "r"(gpub) : "memory");
  }
  mbar_wait(barU + 40, 0);
  bar_sync(9 + wg, 128);
  const uint32_t g3 = gL + T_P3 + 190, g5 = gL + T_P5 + 190, g7 = gL + T_P7 + 126, g9 = gL + T_P9 + 126, gD = gL + T_D + 1118;
  const uint32_t sV = sW;
#define PK4(A, B) pk_bf(A[4 * (B)], A[4 * (B) + 1]), pk_bf(A[4 * (B) + 2], A[4 * (B) + 3]), pk_bf(A[4 * (B) + 4], A[4 * (B) + 5]), pk_bf(A[4 * (B) + 6], A[4 * (B) + 7])
#define PUSHV(V, DST, BAR) \
    asm volatile("st.async.shared::cluster.mbarrier::complete_tx::bytes.v4.b32 [%0], {%1,%2,%3,%4}, [%5];" \
      :: "r"(mapa(DST, rank ^ 1)), "r"(V.x), "r"(V.y), "r"(V.z), "r"(V.w), "r"(mapa(BAR, rank ^ 1)) : "memory");
#define ARRIVE(BAR) if ((tid_now() & 31) == 0) asm volatile("mbarrier.arrive.shared::cta.b64 _, [%0];" :: "r"(BAR) : "memory");

  float acc1[32], accA[24], accB[16], accS[16], accT[8];
  uint32_t raw[10];
  const uint64_t dU = mkdesc(sU, U1_PLANE, 128);
  raw_load<7, 514>(raw, gD, -2, hh);
  {
    uint32_t E[12], E2[12];
    load_E(E, ve0, ve1, ve2, lane);
    dense_group<-1, 3, 2>(acc1, raw, dU);
    dense_load<2, 3>(raw, gD, hh);
    build_V<true>(E, vo8, vo16, vo9);
    if (role < 2) { load_E(E2, ve0 - 512, ve1 - 512, ve2 - 512, lane); build_V<false>(E2, vo8 - 2048, 0, 0); }
    else {
      sts128(sV + l16 + (role & 1) * V5_OFF + 3072, 0, 0, 0, 0);
      if (role == 3 && lane == 0) sts128(sV + V9_OFF + 2 * V9_P, 0, 0, 0, 0);
    }
  }
  dense_group<2, 3, 2>(acc1, raw, dU);
  dense_load<5, 3>(raw, gD, hh);
  dense_group<5, 3, 2>(acc1, raw, dU);
  dense_load<8, 3>(raw, gD, hh);
  asm volatile("fence.proxy.async.shared::cta;" ::: "memory");
  dense_group<8, 3, 2>(acc1, raw, dU);
  dense_load<11, 2>(raw, gD, hh);
  dense_group<11, 2, 2>(acc1, raw, dU);
  dense_load<13, 2>(raw, gD, hh);
  dense_group<13, 2, 2>(acc1, raw, dU);
  dense_load<15, 3>(raw, gD, hh);
  wg_wait<0>();
  redef<28>(acc1);
  dense_group<15, 3, 2>(acc1, raw, dU);
  dense_load<18, 3>(raw, gD, hh);
  dense_group<18, 3, 2>(acc1, raw, dU);
  dense_load<21, 3>(raw, gD, hh);
  bar_sync(9 + wg, 128);
  dense_group<21, 3, 2>(acc1, raw, dU);
  dense_load<24, 3>(raw, gD, hh);
  dense_group<24, 3, 2>(acc1, raw, dU);
  dense_load<27, 3>(raw, gD, hh);
  dense_group<27, 3, 2>(acc1, raw, dU);
  dense_load<30, 2>(raw, gD, hh);
  dense_group<30, 2, 2>(acc1, raw, dU);
  dense_load<32, 2>(raw, gD, hh);
  dense_group<32, 2, 1>(acc1, raw, dU);

  const uint64_t d3 = mkdesc(sV + V3_OFF, 128, 512), d5 = mkdesc(sV + V5_OFF, 128, 512);
  const uint64_t d7 = mkdesc(sV + V7_OFF, 128, V16_P), d9 = mkdesc(sV + V9_OFF, 128, V9_P), d2 = mkdesc(sV + V2_OFF, 128, V16_P);
  uint32_t rb[10];
  raw_load<5>(raw, g3, -2, hh); raw_load<5>(raw + 5, g5, -2, hh);
  raw_load<4>(rb + 1, g3, 3, hh); raw_load<4>(rb + 6, g5, 3, hh);
  rb[0] = cpy(raw[4]); rb[5] = cpy(raw[9]);
  far_group<1, 48, true>(accA, raw, d3, d5);
  raw[0] = cpy(rb[4]); raw[5] = cpy(rb[9]);
  far_group<-1, 48>(accA, rb, d3, d5);
  wg_wait<2>();
  unsigned long long gv;
  asm volatile("ld.relaxed.gpu.global.b64 %0, [%1];" : "=l"(gv) : "l"(P.gate + wg * 512 + rank * 256 + 2 * (tid_now() & 127)) : "memory");
  fence_regs<32>(acc1);
  uint32_t sF, uF, sS3;
  {
    const int ln = tid_now(), mat = (ln >> 3) & 3, r8 = ln & 7;
    const uint32_t uo = (br * 4 + 2 * hh + (mat & 1)) * Y_PLANE + r8 * 16;
    const uint32_t sY = sW + Y_OFF + (1 - (mat >> 1)) * Y_OWN + uo;
    stsm4t(sY, PK4(acc1, 6));
    asm volatile("barrier.cluster.wait.aligned;" ::: "memory");
    __syncwarp();
    stsm4t(sY + 3 * Y_BLK, PK4(acc1, 0)); stsm4t(sY + 2 * Y_BLK, PK4(acc1, 2)); stsm4t(sY + Y_BLK, PK4(acc1, 4));
    {
      const uint4 v = lds128p(!(ln & 16), sW + Y_OFF + (rank ^ 1) * Y_OWN + uo);
      if ((ln & 16) == 0) PUSHV(v, sb + OFF_RAW + wg * Y_OWN + uo, barY + 40)
      ARRIVE(barY + 40)
    }
    raw_load<4>(raw + 1, g3, 7, hh); raw_load<4>(raw + 6, g5, 7, hh);
    far_group<-3, 32, true>(accB, raw, d3, d5);
    asm volatile("fence.proxy.async.shared::cta;" ::: "memory");
    bar_sync(9 + wg, 128);
    if ((ln & 127) == 0) {
      asm volatile("cp.async.bulk.shared::cluster.shared::cta.mbarrier::complete_tx::bytes [%0], [%1], %2, [%3];"
        :: "r"(mapa(sb + OFF_RAW + wg * Y_OWN + Y_BLK, rank ^ 1)), "r"(sW + Y_OFF + (rank ^ 1) * Y_OWN + Y_BLK), "r"(3 * Y_BLK), "r"(mapa(barY, rank ^ 1)) : "memory");
      asm volatile("mbarrier.arrive.shared::cta.b64 _, [%0];" :: "r"(barY) : "memory");
    }
    uF = (br * 4 + (r8 & 3)) * Y_PLANE + (7 - 4 * hh - 2 * (mat & 1) - (r8 >> 2)) * 16;
    sF = sW + F_OFF + (1 - (mat >> 1)) * F_OWN + uF;
    sS3 = (br * 4 + 2 * (r8 & 1) + (mat >> 1)) * Y_PLANE + (7 - 4 * (mat & 1) - (r8 >> 1)) * 16;
  }
  {
    const unsigned tag = (epoch + 1) & 0xFFFFu;
    int it = 0;
    while (((((uint32_t)gv >> 16) != tag) || (((uint32_t)(gv >> 48)) != tag)) && ++it < (1 << 20))
      asm volatile("ld.relaxed.gpu.global.b64 %0, [%1];" : "=l"(gv) : "l"(P.gate + wg * 512 + rank * 256 + 2 * (tid_now() & 127)) : "memory");
  }
  const uint32_t g2 = __byte_perm((uint32_t)gv, (uint32_t)(gv >> 32), 0x5410);
  auto finalize = [&]() {
    uint32_t ya[8], yb[8], f0, f1, ft0, ft1;
    uint4* dst;
    const int tx = tid_now() & 127;
    const uint32_t off = wg * Y_BLK + ((tx >> 2) & 3) * Y_PLANE + (7 - (tx >> 4)) * 16 + (tx & 3) * 4;
    const uint32_t own = sb + OFF_W + Y_OFF + rank * Y_OWN + off, oth = sb + OFF_RAW + off;
    const uint32_t a0 = rank ? oth : own, a1 = rank ? own : oth;
    const uint32_t st0 = rank ? Y_OWN : W_WG, st1 = rank ? W_WG : Y_OWN;
    const uint32_t fown = sb + OFF_W + F_OFF + rank * F_OWN + off, foth = (wg == 1) ? oth + 4 * Y_OWN - Y_BLK : oth + (OFF_FIN - OFF_RAW) - 2 * Y_BLK;
    const uint32_t fst = (wg == 1) ? Y_BLK : 2 * Y_BLK;
    f0 = rank ? foth : fown; f1 = rank ? fown : foth; ft0 = rank ? fst : W_WG; ft1 = rank ? W_WG : fst;
    dst = P.out + (size_t)(wg * 512 + rank * 256 + 2 * tx) * 64 + clus;
    mbar_wait(wg ? barY : barY + 40, 0);
    #pragma unroll
    for (int c = 0; c < 4; c++) {
      ya[c] = lds32(a0 + c * st0); yb[c] = lds32(a0 + c * st0 + 4 * Y_PLANE);
      ya[4 + c] = lds32(a1 + c * st1); yb[4 + c] = lds32(a1 + c * st1 + 4 * Y_PLANE);
    }
    if (wg) {
      mbar_wait(barY + 8 * wg, 0);
      #pragma unroll
      for (int c = 0; c < 4; c++) {
        ya[c] = badd(ya[c], lds32(f0 + c * ft0)); yb[c] = badd(yb[c], lds32(f0 + c * ft0 + 4 * Y_PLANE));
        ya[4 + c] = badd(ya[4 + c], lds32(f1 + c * ft1)); yb[4 + c] = badd(yb[4 + c], lds32(f1 + c * ft1 + 4 * Y_PLANE));
      }
    }
    const uint32_t og = bsub(0x3F803F80u, g2);
    uint32_t o[8];
    #pragma unroll
    for (int c = 0; c < 8; c++) o[c] = badd(bmul(g2, ya[c]), bmul(og, yb[c]));
    if (wg == 0) {
      const uint32_t stg = sb + OFF_U1 + wi * 1024, sw = tx & 4;
      const uint32_t s0 = sw ? 0x7632 : 0x5410, s1 = sw ? 0x5410 : 0x7632, ad = stg + (tx & 31) * 32 + sw * 4;
      sts128(ad, __byte_perm(o[0], o[1], s0), __byte_perm(o[2], o[3], s0), __byte_perm(o[4], o[5], s0), __byte_perm(o[6], o[7], s0));
      sts128(ad ^ 16, __byte_perm(o[0], o[1], s1), __byte_perm(o[2], o[3], s1), __byte_perm(o[4], o[5], s1), __byte_perm(o[6], o[7], s1));
      asm volatile("fence.proxy.async.shared::cta;" ::: "memory");
      __syncwarp();
      if ((tx & 31) == 0) {
        asm volatile("cp.reduce.async.bulk.tensor.2d.global.shared::cta.add.tile.bulk_group [%0, {%2, %3}], [%1];"
          :: "l"(&tmO), "r"(stg), "r"(clus * 8), "r"(wg * 512 + rank * 256 + wq * 64) : "memory");
        asm volatile("cp.async.bulk.commit_group;" ::: "memory");
      }
    } else {
      asm volatile("red.global.add.noftz.v4.bf16x2 [%0], {%1,%2,%3,%4};" :: "l"(dst),
      "r"(__byte_perm(o[0], o[1], 0x5410)), "r"(__byte_perm(o[2], o[3], 0x5410)), "r"(__byte_perm(o[4], o[5], 0x5410)), "r"(__byte_perm(o[6], o[7], 0x5410)) : "memory");
      asm volatile("red.global.add.noftz.v4.bf16x2 [%0], {%1,%2,%3,%4};" :: "l"(dst + 64),
      "r"(__byte_perm(o[0], o[1], 0x7632)), "r"(__byte_perm(o[2], o[3], 0x7632)), "r"(__byte_perm(o[4], o[5], 0x7632)), "r"(__byte_perm(o[6], o[7], 0x7632)) : "memory");
    }
  };
  wg_wait<1>();
  if (wg == 0) finalize();
  fence_regs<24>(accA);
  raw_load<5>(raw, g7, -2, hh); raw_load<5>(raw + 5, g9, -2, hh);
  rb[0] = cpy(raw[4]); rb[5] = cpy(raw[9]);
  const uint32_t f1k = lds32(sT + T_P5 + 64);
  stsm4(sF + Y_BLK, PK4(accA, 4));
  {
    const int ln = tid_now() & 31, df = (ln >> 2) - 2 * (ln & 3);
    const uint32_t b = f1k & 0xFFFFu, dg = (df == 0) ? b : ((df == 1) ? (b << 16) : 0u);
    const Frag f0 = mkfrag(raw, true), f1 = mkfrag(raw + 2, false), f2 = mkfrag(raw + 5, true), f3 = mkfrag(raw + 7, false);
    Frag f4, f5;
    f4.a0 = cpy(hh ? 0u : dg); f4.a1 = cpy(0u); f4.a2 = cpy(0u); f4.a3 = cpy(f4.a0);
    f5.a0 = cpy(hh ? dg : 0u); f5.a1 = cpy(0u); f5.a2 = cpy(0u); f5.a3 = cpy(f5.a0);
    wg_fence();
    far_step<1, 32, true, 2 * V16_P>(accS, f0, d7); far_step<0, 32, false, 2 * V16_P>(accS, f1, d7);
    far_step<1, 32, false, 2 * V16_P>(accS, f2, d9); far_step<0, 32, false, 2 * V16_P>(accS, f3, d9);
    far_step<0, 32>(accS, f4, d2); far_step<1, 32>(accS, f5, d2);
    asm volatile("wgmma.commit_group.sync.aligned;" ::: "memory");
  }
  __syncwarp();
  {
    const uint4 v = lds128p(!(tid_now() & 16), sW + F_OFF + (rank ^ 1) * F_OWN + Y_BLK + uF);
    if ((tid_now() & 16) == 0) PUSHV(v, sb + OFF_RAW + 4 * Y_OWN + wg * Y_BLK + uF, barY + 8)
    ARRIVE(barY + 8)
  }
  wg_wait<1>();
  raw_load<4>(rb + 1, g7, 3, hh); raw_load<4>(rb + 6, g9, 3, hh);
  far_group<-1, 16, true, 2 * V16_P, 2 * V9_P>(accT, rb, d7, d9);
  fence_regs<16>(accB);
  #pragma unroll
  for (int i = 0; i < 16; i++) accA[i] += accB[i];
  stsm4(sF + 3 * Y_BLK, PK4(accA, 0)); stsm4(sF + 2 * Y_BLK, PK4(accA, 2));
  bar_sync(1 + wg * 2 + br, 64);
  uint32_t fp[8];
  const uint32_t aS3 = sW + F_OFF + hh * F_OWN + sS3;
  ldsm4(fp[0], fp[1], fp[2], fp[3], aS3 + 3 * Y_BLK); ldsm4(fp[4], fp[5], fp[6], fp[7], aS3 + 2 * Y_BLK);
  wg_wait<1>();
  fence_regs<16>(accS);
  #pragma unroll
  for (int i = 4; i < 8; i++) { accS[2 * i] += bf_lo(fp[i]); accS[2 * i + 1] += bf_hi(fp[i]); }
  stsm4(aS3 + 2 * Y_BLK, PK4(accS, 2));
  __syncwarp();
  if (hh != rank) { const uint4 v = lds128(aS3 + 2 * Y_BLK); PUSHV(v, sb + OFF_FIN + wg * 2 * Y_BLK + sS3, barY + 16) }
  ARRIVE(barY + 16)
  #pragma unroll
  for (int i = 0; i < 4; i++) { accS[2 * i] += bf_lo(fp[i]); accS[2 * i + 1] += bf_hi(fp[i]); }
  wg_wait<0>();
  fence_regs<8>(accT);
  #pragma unroll
  for (int i = 0; i < 8; i++) accS[i] += accT[i];
  stsm4(aS3 + 3 * Y_BLK, PK4(accS, 0));
  __syncwarp();
  if (hh != rank) { const uint4 v = lds128(aS3 + 3 * Y_BLK); PUSHV(v, sb + OFF_FIN + wg * 2 * Y_BLK + Y_BLK + sS3, barY + 24) }
  ARRIVE(barY + 24)
  if (wg != 0) finalize();
  if (wg == 0 && (tid_now() & 31) == 0) asm volatile("cp.async.bulk.wait_group.read 0;" ::: "memory");
  __syncwarp();
  asm volatile("barrier.cluster.arrive.relaxed.aligned;" ::: "memory");
#undef PK4
#undef PUSHV
#undef ARRIVE
  asm volatile("barrier.cluster.wait.aligned;" ::: "memory");
  if (blockIdx.x == 0 && tid_now() == 0) *P.epoch = epoch + 1;
}

typedef CUresult (*EncodeFn)(CUtensorMap*, CUtensorMapDataType, cuuint32_t, void*, const cuuint64_t*, const cuuint64_t*, const cuuint32_t*,
                             const cuuint32_t*, CUtensorMapInterleave, CUtensorMapSwizzle, CUtensorMapL2promotion, CUtensorMapFloatOOBfill);

}

extern "C" void kernel_launch(void* const* d_in, const int* in_sizes, int n_in, void* d_out, int out_size) {
  static EncodeFn enc = nullptr;
  static unsigned *gate_ptr = nullptr, *epoch_ptr = nullptr;
  if (!enc) {
    cudaGetSymbolAddress((void**)&gate_ptr, g_gate);
    cudaGetSymbolAddress((void**)&epoch_ptr, g_epoch);
    cudaFuncSetAttribute(s4d_kernel, cudaFuncAttributeMaxDynamicSharedMemorySize, SMEM_BYTES);
    void* fn = nullptr; cudaDriverEntryPointQueryResult qr;
    cudaGetDriverEntryPoint("cuTensorMapEncodeTiled", &fn, cudaEnableDefault, &qr);
    enc = (EncodeFn)fn;
  }
  CUtensorMap tm, tmo;
  {
    cuuint64_t gd[2] = {512, 2048}; cuuint64_t gs[1] = {1024}; cuuint32_t box[2] = {8, 256}; cuuint32_t es[2] = {1, 1};
    enc(&tm, CU_TENSOR_MAP_DATA_TYPE_BFLOAT16, 2, d_in[0], gd, gs, box, es, CU_TENSOR_MAP_INTERLEAVE_NONE, CU_TENSOR_MAP_SWIZZLE_NONE,
        CU_TENSOR_MAP_L2_PROMOTION_NONE, CU_TENSOR_MAP_FLOAT_OOB_FILL_NONE);
    box[1] = 64;
    enc(&tmo, CU_TENSOR_MAP_DATA_TYPE_BFLOAT16, 2, d_out, gd, gs, box, es, CU_TENSOR_MAP_INTERLEAVE_NONE, CU_TENSOR_MAP_SWIZZLE_NONE,
        CU_TENSOR_MAP_L2_PROMOTION_NONE, CU_TENSOR_MAP_FLOAT_OOB_FILL_NONE);
  }
  Params P;
  P.u = (const uint4*)d_in[0];
  for (int b = 0; b < 2; b++) {
    P.logA[b] = (const uint32_t*)d_in[1 + 7 * b];
    P.Aim[b] = (const uint32_t*)d_in[2 + 7 * b];
    P.Cre[b] = (const uint32_t*)d_in[3 + 7 * b];
    P.Cim[b] = (const uint32_t*)d_in[4 + 7 * b];
    P.logdt[b] = (const uint16_t*)d_in[5 + 7 * b];
    P.Dsk[b] = (const uint16_t*)d_in[6 + 7 * b];
  }
  P.gw = (const uint4*)d_in[14];
  P.out = (uint4*)d_out;
  P.gate = gate_ptr; P.epoch = epoch_ptr;
  s4d_kernel<<<128, 512, SMEM_BYTES>>>(P, tm, tmo);
}
```
